```python
import torch

def _softmax(x, axis=-1):
    return torch.softmax(x, dim=axis)
def _gelu(x):
    return torch.nn.functional.gelu(x, approximate="tanh")
def _silu(x):
    return torch.nn.functional.silu(x)
def _sigmoid(x):
    return torch.sigmoid(x)
def _layernorm(x, axis=-1, eps=1e-5):
    m = x.mean(dim=axis, keepdim=True)
    v = x.var(dim=axis, keepdim=True, unbiased=False)
    return (x - m) / torch.sqrt(v + eps)
def _scatter_add(tgt, idx, src, axis=0):
    return tgt.clone().index_add_(axis, idx, src)
def _segment_sum(src, seg, n):
    out = torch.zeros((n,) + src.shape[1:], dtype=src.dtype)
    return out.index_add_(0, seg, src)
def _pad(x, pw):
    flat = tuple(v for pair in reversed(pw) for v in pair)
    return torch.nn.functional.pad(x, flat)

kernel_name = 'concat_heads__mha_block_cached__gqa_block_cached__near_ridge'

def setup_inputs():

    _w = (lambda a: (lambda t: t.to(torch.bfloat16) if t.is_floating_point() else t)(torch.as_tensor(a)))
    def _A_setup():
        B, Sq, D = 8, 224, 1024
        H, Sk, Dh = 32, 1024, 128
        return {
            "x": _w((lambda *s: torch.randn(*s, dtype=torch.bfloat16) * 0.8)(B, Sq, D)),
            "k_cache": _w((lambda *s: torch.randn(*s, dtype=torch.bfloat16) * 0.8)(B, H, Sk, Dh)),
            "v_cache": _w((lambda *s: torch.randn(*s, dtype=torch.bfloat16) * 0.05)(B, H, Sk, Dh)),
            "wq": _w((lambda *s: torch.randn(*s, dtype=torch.bfloat16) * 0.8)(D, H * Dh) * (D ** -0.5)),
            "wo": _w((lambda *s: torch.randn(*s, dtype=torch.bfloat16) * 0.05)(H * Dh, D) * ((H * Dh) ** -0.5)),
        }
    _A_in = _A_setup()

    def _B_setup():
        B, Sq, D = 8, 224, 1024
        Hq, Hkv, Sk, Dh = 32, 32, 1024, 128
        assert Hq % Hkv == 0, (Hq, Hkv)
        return {
            "x": _w((lambda *s: torch.randn(*s, dtype=torch.bfloat16) * 0.8)(B, Sq, D)),
            "k_cache": _w((lambda *s: torch.randn(*s, dtype=torch.bfloat16) * 0.8)(B, Hkv, Sk, Dh)),
            "v_cache": _w((lambda *s: torch.randn(*s, dtype=torch.bfloat16) * 0.05)(B, Hkv, Sk, Dh)),
            "wq": _w((lambda *s: torch.randn(*s, dtype=torch.bfloat16) * 0.8)(D, Hq * Dh) * (D ** -0.5)),
            "wo": _w((lambda *s: torch.randn(*s, dtype=torch.bfloat16) * 0.05)(Hq * Dh, D) * ((Hq * Dh) ** -0.5)),
        }
    _B_in = _B_setup()

    return {
        "A_x": _A_in["x"],
        "A_k_cache": _A_in["k_cache"],
        "A_v_cache": _A_in["v_cache"],
        "A_wq": _A_in["wq"],
        "A_wo": _A_in["wo"],
        "B_x": _B_in["x"],
        "B_k_cache": _B_in["k_cache"],
        "B_v_cache": _B_in["v_cache"],
        "B_wq": _B_in["wq"],
        "B_wo": _B_in["wo"],
    }

def reference(A_x, A_k_cache, A_v_cache, A_wq, A_wo, B_x, B_k_cache, B_v_cache, B_wq, B_wo):
    def _A_ref(x, k_cache, v_cache, wq, wo):
        B, Sq, D = x.shape
        H, Dh = 32, 128
        q = (lambda x, *d: x.permute(*d))((x @ wq).reshape(B, Sq, H, Dh), 0, 2, 1, 3)
        scores = torch.einsum("bhqd,bhkd->bhqk", q, k_cache) * (Dh ** -0.5)
        p = _softmax(scores, axis=-1)
        o = torch.einsum("bhqk,bhkd->bhqd", p, v_cache)
        return (lambda x, *d: x.permute(*d))(o, 0, 2, 1, 3).reshape(B, Sq, H * Dh) @ wo

    def _B_ref(x, k_cache, v_cache, wq, wo):
        B, Sq, D = x.shape
        Hq, Dh = 32, 128
        Hkv = k_cache.shape[1]
        rep = Hq // Hkv
        q = (lambda x, *d: x.permute(*d))((x @ wq).reshape(B, Sq, Hq, Dh), 0, 2, 1, 3)
        k = (lambda x, n, axis: torch.repeat_interleave(x, n, dim=axis))(k_cache, rep, axis=1)
        v = (lambda x, n, axis: torch.repeat_interleave(x, n, dim=axis))(v_cache, rep, axis=1)
        scores = torch.einsum("bhqd,bhkd->bhqk", q, k) * (Dh ** -0.5)
        p = _softmax(scores, axis=-1)
        o = torch.einsum("bhqk,bhkd->bhqd", p, v)
        return (lambda x, *d: x.permute(*d))(o, 0, 2, 1, 3).reshape(B, Sq, Hq * Dh) @ wo

    a = _A_ref(A_x, A_k_cache, A_v_cache, A_wq, A_wo)
    b = _B_ref(B_x, B_k_cache, B_v_cache, B_wq, B_wo)
    return torch.concatenate([a, b], axis=-1)
```

```cpp
#include <cuda_runtime.h>
#include <cuda_bf16.h>
#include <cuda.h>
#include <stdint.h>

#define USE_SPARSE 1
#define SLOW_INLINE __forceinline__
#define CREGS 240
#define PREGS (504 - 2 * CREGS)
#define PF_W 0
#define OPROJ_KB 32
#define KV_POL 0x12F0000000000000ull
#define PF_POL KV_POL
#define PF_SKIP 4
#define PF_O 3
#define PF_WJ 9
#define PF_G0 0
#define PF_C 0
#define PF_O0 0
#define KBW kb
#define KBX kb
#define DBG_ROUND 2
#define EARLY_REL 0
#define LEAD_SYNC 1
#define SPLIT0 12
#define SPLIT1 12
#define TOKEN 0
#define PF_X 0
#define PF_X2 -1
#define O_EF 0
#define MAP 0
#define PF_G 1
#define PF_A 0
#define PF_ENABLE 2

namespace {

constexpr int SLOT_BYTES = 32768;
constexpr int NSLOT = 7;
constexpr int BAR_OFF = NSLOT * SLOT_BYTES;
constexpr int SMEM_TOTAL = BAR_OFF + 256 + 1024;
constexpr uint32_t BAR_FULL = 0, BAR_EMPTY = 64, BAR_OST = 128, BAR_FLAG = 144;
constexpr uint32_t SPIN_LIMIT = 1u << 26;
constexpr int NB_QREADY = 1, NB_ORD = 2  , NB_VOTE = 4  , NB_SLOW = 6  , NB_LEAD = 8, NB_TOK = 9;

struct alignas(64) Params {
  CUtensorMap x[2], wq[2], kv[2][2][2]  , wo[2], wo5[2], o_ld, out_st;
  const __nv_bfloat16* kp[2];
  const __nv_bfloat16* vp[2];
  const __nv_bfloat16* wqp[2];
  const __nv_bfloat16* wop[2];
  const __nv_bfloat16* xp[2];
  uint32_t zero;
};

__device__ __nv_bfloat16 g_o[2 * 1792 * 4096];
__device__ unsigned g_flags[64];
__device__ unsigned g_epoch[128];

#define TS(i)
#define TG(i)
#define TF(cond, i)

__device__ __forceinline__ void mma_proj(float (&d)[112], uint64_t da, uint64_t db, int acc) {
  asm volatile("{\n.reg .pred p;\n"
    "setp.ne.b32 p, %114, 0;\n"
    "wgmma.mma_async.sync.aligned.m64n224k16.f32.bf16.bf16 {%0, %1, %2, %3, %4, %5, %6, %7, %8, %9, %10, %11, %12, %13, %14, %15, %16, %17, %18, %19, %20, %21, %22, %23, %24, %25, %26, %27, %28, %29, %30, %31, %32, %33, %34, %35, %36, %37, %38, %39, %40, %41, %42, %43, %44, %45, %46, %47, %48, %49, %50, %51, %52, %53, %54, %55, %56, %57, %58, %59, %60, %61, %62, %63, %64, %65, %66, %67, %68, %69, %70, %71, %72, %73, %74, %75, %76, %77, %78, %79, %80, %81, %82, %83, %84, %85, %86, %87, %88, %89, %90, %91, %92, %93, %94, %95, %96, %97, %98, %99, %100, %101, %102, %103, %104, %105, %106, %107, %108, %109, %110, %111}, %112, %113, p, 1, 1, 1, 0;\n}\n"
    : "+f"(d[0]), "+f"(d[1]), "+f"(d[2]), "+f"(d[3]), "+f"(d[4]), "+f"(d[5]), "+f"(d[6]), "+f"(d[7]), "+f"(d[8]), "+f"(d[9]), "+f"(d[10]), "+f"(d[11]), "+f"(d[12]), "+f"(d[13]), "+f"(d[14]), "+f"(d[15]), "+f"(d[16]), "+f"(d[17]), "+f"(d[18]), "+f"(d[19]), "+f"(d[20]), "+f"(d[21]), "+f"(d[22]), "+f"(d[23]), "+f"(d[24]), "+f"(d[25]), "+f"(d[26]), "+f"(d[27]), "+f"(d[28]), "+f"(d[29]), "+f"(d[30]), "+f"(d[31]), "+f"(d[32]), "+f"(d[33]), "+f"(d[34]), "+f"(d[35]), "+f"(d[36]), "+f"(d[37]), "+f"(d[38]), "+f"(d[39]), "+f"(d[40]), "+f"(d[41]), "+f"(d[42]), "+f"(d[43]), "+f"(d[44]), "+f"(d[45]), "+f"(d[46]), "+f"(d[47]), "+f"(d[48]), "+f"(d[49]), "+f"(d[50]), "+f"(d[51]), "+f"(d[52]), "+f"(d[53]), "+f"(d[54]), "+f"(d[55]), "+f"(d[56]), "+f"(d[57]), "+f"(d[58]), "+f"(d[59]), "+f"(d[60]), "+f"(d[61]), "+f"(d[62]), "+f"(d[63]), "+f"(d[64]), "+f"(d[65]), "+f"(d[66]), "+f"(d[67]), "+f"(d[68]), "+f"(d[69]), "+f"(d[70]), "+f"(d[71]), "+f"(d[72]), "+f"(d[73]), "+f"(d[74]), "+f"(d[75]), "+f"(d[76]), "+f"(d[77]), "+f"(d[78]), "+f"(d[79]), "+f"(d[80]), "+f"(d[81]), "+f"(d[82]), "+f"(d[83]), "+f"(d[84]), "+f"(d[85]), "+f"(d[86]), "+f"(d[87]), "+f"(d[88]), "+f"(d[89]), "+f"(d[90]), "+f"(d[91]), "+f"(d[92]), "+f"(d[93]), "+f"(d[94]), "+f"(d[95]), "+f"(d[96]), "+f"(d[97]), "+f"(d[98]), "+f"(d[99]), "+f"(d[100]), "+f"(d[101]), "+f"(d[102]), "+f"(d[103]), "+f"(d[104]), "+f"(d[105]), "+f"(d[106]), "+f"(d[107]), "+f"(d[108]), "+f"(d[109]), "+f"(d[110]), "+f"(d[111])
    : "l"(da), "l"(db), "r"(acc));
}
__device__ __forceinline__ void mma_proj0(float (&d)[112], uint64_t da, uint64_t db, int acc) {
  asm volatile("{\n.reg .pred p;\n"
    "setp.ne.b32 p, %114, 0;\n"
    "wgmma.mma_async.sync.aligned.m64n224k16.f32.bf16.bf16 {%0, %1, %2, %3, %4, %5, %6, %7, %8, %9, %10, %11, %12, %13, %14, %15, %16, %17, %18, %19, %20, %21, %22, %23, %24, %25, %26, %27, %28, %29, %30, %31, %32, %33, %34, %35, %36, %37, %38, %39, %40, %41, %42, %43, %44, %45, %46, %47, %48, %49, %50, %51, %52, %53, %54, %55, %56, %57, %58, %59, %60, %61, %62, %63, %64, %65, %66, %67, %68, %69, %70, %71, %72, %73, %74, %75, %76, %77, %78, %79, %80, %81, %82, %83, %84, %85, %86, %87, %88, %89, %90, %91, %92, %93, %94, %95, %96, %97, %98, %99, %100, %101, %102, %103, %104, %105, %106, %107, %108, %109, %110, %111}, %112, %113, p, 1, 1, 1, 0;\n}\n"
    : "=f"(d[0]), "=f"(d[1]), "=f"(d[2]), "=f"(d[3]), "=f"(d[4]), "=f"(d[5]), "=f"(d[6]), "=f"(d[7]), "=f"(d[8]), "=f"(d[9]), "=f"(d[10]), "=f"(d[11]), "=f"(d[12]), "=f"(d[13]), "=f"(d[14]), "=f"(d[15]), "=f"(d[16]), "=f"(d[17]), "=f"(d[18]), "=f"(d[19]), "=f"(d[20]), "=f"(d[21]), "=f"(d[22]), "=f"(d[23]), "=f"(d[24]), "=f"(d[25]), "=f"(d[26]), "=f"(d[27]), "=f"(d[28]), "=f"(d[29]), "=f"(d[30]), "=f"(d[31]), "=f"(d[32]), "=f"(d[33]), "=f"(d[34]), "=f"(d[35]), "=f"(d[36]), "=f"(d[37]), "=f"(d[38]), "=f"(d[39]), "=f"(d[40]), "=f"(d[41]), "=f"(d[42]), "=f"(d[43]), "=f"(d[44]), "=f"(d[45]), "=f"(d[46]), "=f"(d[47]), "=f"(d[48]), "=f"(d[49]), "=f"(d[50]), "=f"(d[51]), "=f"(d[52]), "=f"(d[53]), "=f"(d[54]), "=f"(d[55]), "=f"(d[56]), "=f"(d[57]), "=f"(d[58]), "=f"(d[59]), "=f"(d[60]), "=f"(d[61]), "=f"(d[62]), "=f"(d[63]), "=f"(d[64]), "=f"(d[65]), "=f"(d[66]), "=f"(d[67]), "=f"(d[68]), "=f"(d[69]), "=f"(d[70]), "=f"(d[71]), "=f"(d[72]), "=f"(d[73]), "=f"(d[74]), "=f"(d[75]), "=f"(d[76]), "=f"(d[77]), "=f"(d[78]), "=f"(d[79]), "=f"(d[80]), "=f"(d[81]), "=f"(d[82]), "=f"(d[83]), "=f"(d[84]), "=f"(d[85]), "=f"(d[86]), "=f"(d[87]), "=f"(d[88]), "=f"(d[89]), "=f"(d[90]), "=f"(d[91]), "=f"(d[92]), "=f"(d[93]), "=f"(d[94]), "=f"(d[95]), "=f"(d[96]), "=f"(d[97]), "=f"(d[98]), "=f"(d[99]), "=f"(d[100]), "=f"(d[101]), "=f"(d[102]), "=f"(d[103]), "=f"(d[104]), "=f"(d[105]), "=f"(d[106]), "=f"(d[107]), "=f"(d[108]), "=f"(d[109]), "=f"(d[110]), "=f"(d[111])
    : "l"(da), "l"(db), "r"(acc));
}
__device__ __forceinline__ void mma_qk(float (&d)[48], uint64_t da, uint64_t db, int acc) {
  asm volatile("{\n.reg .pred p;\n"
    "setp.ne.b32 p, %50, 0;\n"
    "wgmma.mma_async.sync.aligned.m64n96k16.f32.bf16.bf16 {%0, %1, %2, %3, %4, %5, %6, %7, %8, %9, %10, %11, %12, %13, %14, %15, %16, %17, %18, %19, %20, %21, %22, %23, %24, %25, %26, %27, %28, %29, %30, %31, %32, %33, %34, %35, %36, %37, %38, %39, %40, %41, %42, %43, %44, %45, %46, %47}, %48, %49, p, 1, 1, 1, 0;\n}\n"
    : "+f"(d[0]), "+f"(d[1]), "+f"(d[2]), "+f"(d[3]), "+f"(d[4]), "+f"(d[5]), "+f"(d[6]), "+f"(d[7]), "+f"(d[8]), "+f"(d[9]), "+f"(d[10]), "+f"(d[11]), "+f"(d[12]), "+f"(d[13]), "+f"(d[14]), "+f"(d[15]), "+f"(d[16]), "+f"(d[17]), "+f"(d[18]), "+f"(d[19]), "+f"(d[20]), "+f"(d[21]), "+f"(d[22]), "+f"(d[23]), "+f"(d[24]), "+f"(d[25]), "+f"(d[26]), "+f"(d[27]), "+f"(d[28]), "+f"(d[29]), "+f"(d[30]), "+f"(d[31]), "+f"(d[32]), "+f"(d[33]), "+f"(d[34]), "+f"(d[35]), "+f"(d[36]), "+f"(d[37]), "+f"(d[38]), "+f"(d[39]), "+f"(d[40]), "+f"(d[41]), "+f"(d[42]), "+f"(d[43]), "+f"(d[44]), "+f"(d[45]), "+f"(d[46]), "+f"(d[47])
    : "l"(da), "l"(db), "r"(acc));
}
__device__ __forceinline__ void mma_qk0(float (&d)[48], uint64_t da, uint64_t db, int acc) {
  asm volatile("{\n.reg .pred p;\n"
    "setp.ne.b32 p, %50, 0;\n"
    "wgmma.mma_async.sync.aligned.m64n96k16.f32.bf16.bf16 {%0, %1, %2, %3, %4, %5, %6, %7, %8, %9, %10, %11, %12, %13, %14, %15, %16, %17, %18, %19, %20, %21, %22, %23, %24, %25, %26, %27, %28, %29, %30, %31, %32, %33, %34, %35, %36, %37, %38, %39, %40, %41, %42, %43, %44, %45, %46, %47}, %48, %49, p, 1, 1, 1, 0;\n}\n"
    : "=f"(d[0]), "=f"(d[1]), "=f"(d[2]), "=f"(d[3]), "=f"(d[4]), "=f"(d[5]), "=f"(d[6]), "=f"(d[7]), "=f"(d[8]), "=f"(d[9]), "=f"(d[10]), "=f"(d[11]), "=f"(d[12]), "=f"(d[13]), "=f"(d[14]), "=f"(d[15]), "=f"(d[16]), "=f"(d[17]), "=f"(d[18]), "=f"(d[19]), "=f"(d[20]), "=f"(d[21]), "=f"(d[22]), "=f"(d[23]), "=f"(d[24]), "=f"(d[25]), "=f"(d[26]), "=f"(d[27]), "=f"(d[28]), "=f"(d[29]), "=f"(d[30]), "=f"(d[31]), "=f"(d[32]), "=f"(d[33]), "=f"(d[34]), "=f"(d[35]), "=f"(d[36]), "=f"(d[37]), "=f"(d[38]), "=f"(d[39]), "=f"(d[40]), "=f"(d[41]), "=f"(d[42]), "=f"(d[43]), "=f"(d[44]), "=f"(d[45]), "=f"(d[46]), "=f"(d[47])
    : "l"(da), "l"(db), "r"(acc));
}
__device__ __forceinline__ void mma_qk_sp(float (&d)[48], uint64_t da, uint64_t db, int acc, uint32_t meta) {
  asm volatile("{\n.reg .pred p;\n"
    "setp.ne.b32 p, %50, 0;\n"
    "wgmma.mma_async.sp.sync.aligned.m64n96k32.f32.bf16.bf16 {%0, %1, %2, %3, %4, %5, %6, %7, %8, %9, %10, %11, %12, %13, %14, %15, %16, %17, %18, %19, %20, %21, %22, %23, %24, %25, %26, %27, %28, %29, %30, %31, %32, %33, %34, %35, %36, %37, %38, %39, %40, %41, %42, %43, %44, %45, %46, %47}, %48, %49, %51, 0, p, 1, 1, 1, 0;\n}\n"
    : "+f"(d[0]), "+f"(d[1]), "+f"(d[2]), "+f"(d[3]), "+f"(d[4]), "+f"(d[5]), "+f"(d[6]), "+f"(d[7]), "+f"(d[8]), "+f"(d[9]), "+f"(d[10]), "+f"(d[11]), "+f"(d[12]), "+f"(d[13]), "+f"(d[14]), "+f"(d[15]), "+f"(d[16]), "+f"(d[17]), "+f"(d[18]), "+f"(d[19]), "+f"(d[20]), "+f"(d[21]), "+f"(d[22]), "+f"(d[23]), "+f"(d[24]), "+f"(d[25]), "+f"(d[26]), "+f"(d[27]), "+f"(d[28]), "+f"(d[29]), "+f"(d[30]), "+f"(d[31]), "+f"(d[32]), "+f"(d[33]), "+f"(d[34]), "+f"(d[35]), "+f"(d[36]), "+f"(d[37]), "+f"(d[38]), "+f"(d[39]), "+f"(d[40]), "+f"(d[41]), "+f"(d[42]), "+f"(d[43]), "+f"(d[44]), "+f"(d[45]), "+f"(d[46]), "+f"(d[47])
    : "l"(da), "l"(db), "r"(acc), "r"(meta));
}
__device__ __forceinline__ void mma_qk_sp0(float (&d)[48], uint64_t da, uint64_t db, int acc, uint32_t meta) {
  asm volatile("{\n.reg .pred p;\n"
    "setp.ne.b32 p, %50, 0;\n"
    "wgmma.mma_async.sp.sync.aligned.m64n96k32.f32.bf16.bf16 {%0, %1, %2, %3, %4, %5, %6, %7, %8, %9, %10, %11, %12, %13, %14, %15, %16, %17, %18, %19, %20, %21, %22, %23, %24, %25, %26, %27, %28, %29, %30, %31, %32, %33, %34, %35, %36, %37, %38, %39, %40, %41, %42, %43, %44, %45, %46, %47}, %48, %49, %51, 0, p, 1, 1, 1, 0;\n}\n"
    : "=f"(d[0]), "=f"(d[1]), "=f"(d[2]), "=f"(d[3]), "=f"(d[4]), "=f"(d[5]), "=f"(d[6]), "=f"(d[7]), "=f"(d[8]), "=f"(d[9]), "=f"(d[10]), "=f"(d[11]), "=f"(d[12]), "=f"(d[13]), "=f"(d[14]), "=f"(d[15]), "=f"(d[16]), "=f"(d[17]), "=f"(d[18]), "=f"(d[19]), "=f"(d[20]), "=f"(d[21]), "=f"(d[22]), "=f"(d[23]), "=f"(d[24]), "=f"(d[25]), "=f"(d[26]), "=f"(d[27]), "=f"(d[28]), "=f"(d[29]), "=f"(d[30]), "=f"(d[31]), "=f"(d[32]), "=f"(d[33]), "=f"(d[34]), "=f"(d[35]), "=f"(d[36]), "=f"(d[37]), "=f"(d[38]), "=f"(d[39]), "=f"(d[40]), "=f"(d[41]), "=f"(d[42]), "=f"(d[43]), "=f"(d[44]), "=f"(d[45]), "=f"(d[46]), "=f"(d[47])
    : "l"(da), "l"(db), "r"(acc), "r"(meta));
}
__device__ __forceinline__ void mma_qk(float (&d)[32], uint64_t da, uint64_t db, int acc) {
  asm volatile("{\n.reg .pred p;\n"
    "setp.ne.b32 p, %34, 0;\n"
    "wgmma.mma_async.sync.aligned.m64n64k16.f32.bf16.bf16 {%0, %1, %2, %3, %4, %5, %6, %7, %8, %9, %10, %11, %12, %13, %14, %15, %16, %17, %18, %19, %20, %21, %22, %23, %24, %25, %26, %27, %28, %29, %30, %31}, %32, %33, p, 1, 1, 1, 0;\n}\n"
    : "+f"(d[0]), "+f"(d[1]), "+f"(d[2]), "+f"(d[3]), "+f"(d[4]), "+f"(d[5]), "+f"(d[6]), "+f"(d[7]), "+f"(d[8]), "+f"(d[9]), "+f"(d[10]), "+f"(d[11]), "+f"(d[12]), "+f"(d[13]), "+f"(d[14]), "+f"(d[15]), "+f"(d[16]), "+f"(d[17]), "+f"(d[18]), "+f"(d[19]), "+f"(d[20]), "+f"(d[21]), "+f"(d[22]), "+f"(d[23]), "+f"(d[24]), "+f"(d[25]), "+f"(d[26]), "+f"(d[27]), "+f"(d[28]), "+f"(d[29]), "+f"(d[30]), "+f"(d[31])
    : "l"(da), "l"(db), "r"(acc));
}
__device__ __forceinline__ void mma_qk0(float (&d)[32], uint64_t da, uint64_t db, int acc) {
  asm volatile("{\n.reg .pred p;\n"
    "setp.ne.b32 p, %34, 0;\n"
    "wgmma.mma_async.sync.aligned.m64n64k16.f32.bf16.bf16 {%0, %1, %2, %3, %4, %5, %6, %7, %8, %9, %10, %11, %12, %13, %14, %15, %16, %17, %18, %19, %20, %21, %22, %23, %24, %25, %26, %27, %28, %29, %30, %31}, %32, %33, p, 1, 1, 1, 0;\n}\n"
    : "=f"(d[0]), "=f"(d[1]), "=f"(d[2]), "=f"(d[3]), "=f"(d[4]), "=f"(d[5]), "=f"(d[6]), "=f"(d[7]), "=f"(d[8]), "=f"(d[9]), "=f"(d[10]), "=f"(d[11]), "=f"(d[12]), "=f"(d[13]), "=f"(d[14]), "=f"(d[15]), "=f"(d[16]), "=f"(d[17]), "=f"(d[18]), "=f"(d[19]), "=f"(d[20]), "=f"(d[21]), "=f"(d[22]), "=f"(d[23]), "=f"(d[24]), "=f"(d[25]), "=f"(d[26]), "=f"(d[27]), "=f"(d[28]), "=f"(d[29]), "=f"(d[30]), "=f"(d[31])
    : "l"(da), "l"(db), "r"(acc));
}
__device__ __forceinline__ void mma_qk_sp(float (&d)[32], uint64_t da, uint64_t db, int acc, uint32_t meta) {
  asm volatile("{\n.reg .pred p;\n"
    "setp.ne.b32 p, %34, 0;\n"
    "wgmma.mma_async.sp.sync.aligned.m64n64k32.f32.bf16.bf16 {%0, %1, %2, %3, %4, %5, %6, %7, %8, %9, %10, %11, %12, %13, %14, %15, %16, %17, %18, %19, %20, %21, %22, %23, %24, %25, %26, %27, %28, %29, %30, %31}, %32, %33, %35, 0, p, 1, 1, 1, 0;\n}\n"
    : "+f"(d[0]), "+f"(d[1]), "+f"(d[2]), "+f"(d[3]), "+f"(d[4]), "+f"(d[5]), "+f"(d[6]), "+f"(d[7]), "+f"(d[8]), "+f"(d[9]), "+f"(d[10]), "+f"(d[11]), "+f"(d[12]), "+f"(d[13]), "+f"(d[14]), "+f"(d[15]), "+f"(d[16]), "+f"(d[17]), "+f"(d[18]), "+f"(d[19]), "+f"(d[20]), "+f"(d[21]), "+f"(d[22]), "+f"(d[23]), "+f"(d[24]), "+f"(d[25]), "+f"(d[26]), "+f"(d[27]), "+f"(d[28]), "+f"(d[29]), "+f"(d[30]), "+f"(d[31])
    : "l"(da), "l"(db), "r"(acc), "r"(meta));
}
__device__ __forceinline__ void mma_qk_sp0(float (&d)[32], uint64_t da, uint64_t db, int acc, uint32_t meta) {
  asm volatile("{\n.reg .pred p;\n"
    "setp.ne.b32 p, %34, 0;\n"
    "wgmma.mma_async.sp.sync.aligned.m64n64k32.f32.bf16.bf16 {%0, %1, %2, %3, %4, %5, %6, %7, %8, %9, %10, %11, %12, %13, %14, %15, %16, %17, %18, %19, %20, %21, %22, %23, %24, %25, %26, %27, %28, %29, %30, %31}, %32, %33, %35, 0, p, 1, 1, 1, 0;\n}\n"
    : "=f"(d[0]), "=f"(d[1]), "=f"(d[2]), "=f"(d[3]), "=f"(d[4]), "=f"(d[5]), "=f"(d[6]), "=f"(d[7]), "=f"(d[8]), "=f"(d[9]), "=f"(d[10]), "=f"(d[11]), "=f"(d[12]), "=f"(d[13]), "=f"(d[14]), "=f"(d[15]), "=f"(d[16]), "=f"(d[17]), "=f"(d[18]), "=f"(d[19]), "=f"(d[20]), "=f"(d[21]), "=f"(d[22]), "=f"(d[23]), "=f"(d[24]), "=f"(d[25]), "=f"(d[26]), "=f"(d[27]), "=f"(d[28]), "=f"(d[29]), "=f"(d[30]), "=f"(d[31])
    : "l"(da), "l"(db), "r"(acc), "r"(meta));
}
__device__ __forceinline__ void mma_pv(float (&d)[64], uint32_t a0, uint32_t a1, uint32_t a2, uint32_t a3, uint64_t db, int acc) {
  asm volatile("{\n.reg .pred p;\n"
    "setp.ne.b32 p, %69, 0;\n"
    "wgmma.mma_async.sync.aligned.m64n128k16.f32.bf16.bf16 {%0, %1, %2, %3, %4, %5, %6, %7, %8, %9, %10, %11, %12, %13, %14, %15, %16, %17, %18, %19, %20, %21, %22, %23, %24, %25, %26, %27, %28, %29, %30, %31, %32, %33, %34, %35, %36, %37, %38, %39, %40, %41, %42, %43, %44, %45, %46, %47, %48, %49, %50, %51, %52, %53, %54, %55, %56, %57, %58, %59, %60, %61, %62, %63}, {%64, %65, %66, %67}, %68, p, 1, 1, 1;\n}\n"
    : "+f"(d[0]), "+f"(d[1]), "+f"(d[2]), "+f"(d[3]), "+f"(d[4]), "+f"(d[5]), "+f"(d[6]), "+f"(d[7]), "+f"(d[8]), "+f"(d[9]), "+f"(d[10]), "+f"(d[11]), "+f"(d[12]), "+f"(d[13]), "+f"(d[14]), "+f"(d[15]), "+f"(d[16]), "+f"(d[17]), "+f"(d[18]), "+f"(d[19]), "+f"(d[20]), "+f"(d[21]), "+f"(d[22]), "+f"(d[23]), "+f"(d[24]), "+f"(d[25]), "+f"(d[26]), "+f"(d[27]), "+f"(d[28]), "+f"(d[29]), "+f"(d[30]), "+f"(d[31]), "+f"(d[32]), "+f"(d[33]), "+f"(d[34]), "+f"(d[35]), "+f"(d[36]), "+f"(d[37]), "+f"(d[38]), "+f"(d[39]), "+f"(d[40]), "+f"(d[41]), "+f"(d[42]), "+f"(d[43]), "+f"(d[44]), "+f"(d[45]), "+f"(d[46]), "+f"(d[47]), "+f"(d[48]), "+f"(d[49]), "+f"(d[50]), "+f"(d[51]), "+f"(d[52]), "+f"(d[53]), "+f"(d[54]), "+f"(d[55]), "+f"(d[56]), "+f"(d[57]), "+f"(d[58]), "+f"(d[59]), "+f"(d[60]), "+f"(d[61]), "+f"(d[62]), "+f"(d[63])
    : "r"(a0), "r"(a1), "r"(a2), "r"(a3), "l"(db), "r"(acc));
}
__device__ __forceinline__ void mma_pv_sp(float (&d)[64], uint32_t a0, uint32_t a1, uint32_t a2, uint32_t a3, uint64_t db, int acc, uint32_t meta) {
  asm volatile("{\n.reg .pred p;\n"
    "setp.ne.b32 p, %69, 0;\n"
    "wgmma.mma_async.sp.sync.aligned.m64n128k32.f32.bf16.bf16 {%0, %1, %2, %3, %4, %5, %6, %7, %8, %9, %10, %11, %12, %13, %14, %15, %16, %17, %18, %19, %20, %21, %22, %23, %24, %25, %26, %27, %28, %29, %30, %31, %32, %33, %34, %35, %36, %37, %38, %39, %40, %41, %42, %43, %44, %45, %46, %47, %48, %49, %50, %51, %52, %53, %54, %55, %56, %57, %58, %59, %60, %61, %62, %63}, {%64, %65, %66, %67}, %68, %70, 0, p, 1, 1, 1;\n}\n"
    : "+f"(d[0]), "+f"(d[1]), "+f"(d[2]), "+f"(d[3]), "+f"(d[4]), "+f"(d[5]), "+f"(d[6]), "+f"(d[7]), "+f"(d[8]), "+f"(d[9]), "+f"(d[10]), "+f"(d[11]), "+f"(d[12]), "+f"(d[13]), "+f"(d[14]), "+f"(d[15]), "+f"(d[16]), "+f"(d[17]), "+f"(d[18]), "+f"(d[19]), "+f"(d[20]), "+f"(d[21]), "+f"(d[22]), "+f"(d[23]), "+f"(d[24]), "+f"(d[25]), "+f"(d[26]), "+f"(d[27]), "+f"(d[28]), "+f"(d[29]), "+f"(d[30]), "+f"(d[31]), "+f"(d[32]), "+f"(d[33]), "+f"(d[34]), "+f"(d[35]), "+f"(d[36]), "+f"(d[37]), "+f"(d[38]), "+f"(d[39]), "+f"(d[40]), "+f"(d[41]), "+f"(d[42]), "+f"(d[43]), "+f"(d[44]), "+f"(d[45]), "+f"(d[46]), "+f"(d[47]), "+f"(d[48]), "+f"(d[49]), "+f"(d[50]), "+f"(d[51]), "+f"(d[52]), "+f"(d[53]), "+f"(d[54]), "+f"(d[55]), "+f"(d[56]), "+f"(d[57]), "+f"(d[58]), "+f"(d[59]), "+f"(d[60]), "+f"(d[61]), "+f"(d[62]), "+f"(d[63])
    : "r"(a0), "r"(a1), "r"(a2), "r"(a3), "l"(db), "r"(acc), "r"(meta));
}

__device__ __forceinline__ uint32_t vbid() {
  return blockIdx.x;
}
__device__ __forceinline__ uint32_t smem_u32(const void* p) { return (uint32_t)__cvta_generic_to_shared(p); }
__device__ __forceinline__ void wg_fence() { asm volatile("wgmma.fence.sync.aligned;" ::: "memory"); }
__device__ __forceinline__ void wg_commit() { asm volatile("wgmma.commit_group.sync.aligned;" ::: "memory"); }
template <int N> __device__ __forceinline__ void wg_wait() { asm volatile("wgmma.wait_group.sync.aligned %0;" ::"n"(N) : "memory"); }
template <int N> __device__ __forceinline__ void pin(float (&d)[N]) {
#pragma unroll
  for (int i = 0; i < N; i++) asm volatile("" : "+f"(d[i])::"memory");
}
__device__ __forceinline__ uint64_t desc(uint32_t lo) { return ((uint64_t)0x40000040u << 32) | lo; }
__device__ __forceinline__ void mbar_init(uint32_t bar, int cnt) { asm volatile("mbarrier.init.shared::cta.b64 [%0], %1;" ::"r"(bar), "r"(cnt) : "memory"); }
__device__ __forceinline__ void mbar_expect_tx(uint32_t bar, uint32_t bytes) {
  asm volatile("mbarrier.arrive.expect_tx.shared::cta.b64 _, [%0], %1;" ::"r"(bar), "r"(bytes) : "memory");
}
__device__ __forceinline__ void mbar_wait(uint32_t bar, uint32_t parity) {
  asm volatile(
      "{\n.reg .pred p;\n.reg .u32 n;\n"
      "mbarrier.try_wait.parity.shared::cta.b64 p, [%0], %1;\n"
      "@p bra DONE;\n"
      "mov.u32 n, 0;\n"
      "SPIN:\n"
      "mbarrier.try_wait.parity.shared::cta.b64 p, [%0], %1;\n"
      "@p bra DONE;\n"
      "add.u32 n, n, 1;\n"
      "setp.lt.u32 p, n, %2;\n"
      "@p bra SPIN;\n"
      "trap;\n"
      "DONE:\n}\n" ::"r"(bar), "r"(parity), "n"(SPIN_LIMIT) : "memory");
}
__device__ __forceinline__ bool mbar_test(uint32_t bar, uint32_t parity) {
  uint32_t ok;
  asm volatile("{\n.reg .pred p;\nmbarrier.test_wait.parity.shared::cta.b64 p, [%1], %2;\nselp.u32 %0, 1, 0, p;\n}\n" : "=r"(ok) : "r"(bar), "r"(parity) : "memory");
  return ok;
}
__device__ __forceinline__ void mbar_arrive(uint32_t bar) { asm volatile("mbarrier.arrive.shared::cta.b64 _, [%0];" ::"r"(bar) : "memory"); }
__device__ __forceinline__ void mbar_arrive_cluster(uint32_t addr) { asm volatile("mbarrier.arrive.shared::cluster.b64 _, [%0];" ::"r"(addr) : "memory"); }
__device__ __forceinline__ uint32_t mapa(uint32_t addr, uint32_t rank) {
  uint32_t r;
  asm("mapa.shared::cluster.u32 %0, %1, %2;" : "=r"(r) : "r"(addr), "r"(rank));
  return r;
}
__device__ __forceinline__ void tma_load(uint32_t dst, const CUtensorMap* m, int c0, int c1, uint32_t bar) {
  asm volatile("cp.async.bulk.tensor.2d.shared::cluster.global.mbarrier::complete_tx::bytes [%0], [%1, {%3, %4}], [%2];" ::"r"(dst), "l"(m), "r"(bar), "r"(c0), "r"(c1) : "memory");
}
__device__ __forceinline__ void tma_load5(uint32_t dst, const CUtensorMap* m, int c0, int c4, uint32_t bar) {
  asm volatile("cp.async.bulk.tensor.5d.shared::cluster.global.mbarrier::complete_tx::bytes [%0], [%1, {%3, %5, %5, %5, %4}], [%2];" ::"r"(dst), "l"(m), "r"(bar), "r"(c0), "r"(c4), "r"(0) : "memory");
}
__device__ __forceinline__ void tma_load_hint(uint32_t dst, const CUtensorMap* m, int c0, int c1, uint32_t bar, uint64_t pol) {
  asm volatile("cp.async.bulk.tensor.2d.shared::cluster.global.mbarrier::complete_tx::bytes.L2::cache_hint [%0], [%1, {%3, %4}], [%2], %5;" ::"r"(dst), "l"(m), "r"(bar), "r"(c0), "r"(c1), "l"(pol) : "memory");
}
__device__ __forceinline__ void tma_load_mc(uint32_t dst, const CUtensorMap* m, int c0, int c1, uint32_t bar) {
  asm volatile("cp.async.bulk.tensor.2d.shared::cluster.global.mbarrier::complete_tx::bytes.multicast::cluster [%0], [%1, {%3, %4}], [%2], %5;" ::"r"(dst), "l"(m), "r"(bar), "r"(c0), "r"(c1), "h"((uint16_t)3) : "memory");
}
__device__ __forceinline__ void tma_store(const CUtensorMap* m, int c0, int c1, uint32_t src) {
  asm volatile("cp.async.bulk.tensor.2d.global.shared::cta.bulk_group [%0, {%2, %3}], [%1];" ::"l"(m), "r"(src), "r"(c0), "r"(c1) : "memory");
}
__device__ __forceinline__ void tma_store_hint(const CUtensorMap* m, int c0, int c1, uint32_t src, uint64_t pol) {
  asm volatile("cp.async.bulk.tensor.2d.global.shared::cta.bulk_group.L2::cache_hint [%0, {%2, %3}], [%1], %4;" ::"l"(m), "r"(src), "r"(c0), "r"(c1), "l"(pol) : "memory");
}
__device__ __forceinline__ void l2_prefetch(const void* p, uint32_t bytes) {
  asm volatile("cp.async.bulk.prefetch.L2.global [%0], %1;" ::"l"(p), "r"(bytes) : "memory");
}
__device__ __forceinline__ void tma_prefetch(const CUtensorMap* m, int c0, int c1) {
  asm volatile("cp.async.bulk.prefetch.tensor.2d.L2.global [%0, {%1, %2}];" ::"l"(m), "r"(c0), "r"(c1) : "memory");
}
__device__ __forceinline__ void fence_async_smem() { asm volatile("fence.proxy.async.shared::cta;" ::: "memory"); }
__device__ __forceinline__ void bar_sync(int id, int n) { asm volatile("bar.sync %0, %1;" ::"r"(id), "r"(n) : "memory"); }
__device__ __forceinline__ void bar_arrive(int id, int n) { asm volatile("bar.arrive %0, %1;" ::"r"(id), "r"(n) : "memory"); }
__device__ __forceinline__ bool bar_any(int id, int n, bool v) {
  uint32_t r;
  asm volatile("{\n.reg .pred p, q;\nsetp.ne.u32 q, %3, 0;\nbar.red.or.pred p, %1, %2, q;\nselp.u32 %0, 1, 0, p;\n}\n" : "=r"(r) : "r"(id), "r"(n), "r"((uint32_t)v) : "memory");
  return r;
}
__device__ __forceinline__ void cluster_arrive() { asm volatile("barrier.cluster.arrive.relaxed.aligned;" ::: "memory"); }
__device__ __forceinline__ void cluster_wait() { asm volatile("barrier.cluster.wait.aligned;" ::: "memory"); }
__device__ __forceinline__ float ex2(float x) {
  float y;
  asm("ex2.approx.ftz.f32 %0, %1;" : "=f"(y) : "f"(x));
  return y;
}
__device__ __forceinline__ uint32_t pack(float lo, float hi) {
  uint32_t p;
  asm("cvt.rn.bf16x2.f32 %0, %1, %2;" : "=r"(p) : "f"(hi), "f"(lo));
  return p;
}
__device__ __forceinline__ void stsm4(uint32_t addr, uint32_t r0, uint32_t r1, uint32_t r2, uint32_t r3) {
  asm volatile("stmatrix.sync.aligned.m8n8.x4.shared.b16 [%0], {%1, %2, %3, %4};" ::"r"(addr), "r"(r0), "r"(r1), "r"(r2), "r"(r3) : "memory");
}
__device__ __forceinline__ void stsm4t(uint32_t addr, uint32_t r0, uint32_t r1, uint32_t r2, uint32_t r3) {
  asm volatile("stmatrix.sync.aligned.m8n8.x4.trans.shared.b16 [%0], {%1, %2, %3, %4};" ::"r"(addr), "r"(r0), "r"(r1), "r"(r2), "r"(r3) : "memory");
}
__device__ __forceinline__ uint32_t opaque_tid() {
  uint32_t t;
  asm volatile("mov.u32 %0, %%tid.x;" : "=r"(t));
  return t;
}

struct Cursor {
  uint32_t s, par;
  template <int N> __device__ __forceinline__ void next() {
    if (N == 5 && s == 3) { s = 6; return; }
    if (++s == 7) { s = 0; par ^= 1; }
  }
};
__device__ __forceinline__ bool elect_one() {
  uint32_t r;
  asm volatile("{\n.reg .pred p;\nelect.sync _|p, 0xffffffff;\nselp.u32 %0, 1, 0, p;\n}\n" : "=r"(r));
  return r;
}

__device__ SLOW_INLINE void slow_rows(uint32_t qreg  , int w,
                                       const __nv_bfloat16* __restrict__ K, const __nv_bfloat16* __restrict__ V, __nv_bfloat16* out) {
  const int t = threadIdx.x & 127;
  const bool active = (w == 0) || (t < 96);
  const int tile = t >> 6, r = t & 63;
  uint32_t q2[64];
#pragma unroll
  for (int d = 0; d < 128; d++) {
    uint32_t addr;
    if (USE_SPARSE && w == 1 && tile == 1) {
      const int kap = 16 * (d >> 5) + 2 * ((d & 31) >> 2) + (d & 1), h = ((d >> 1) ^ (d >> 3)) & 1;
      const int chunk = 2 * ((r >> 3) & 3) + h;
      addr = qreg + 16384 + kap * 128 + ((chunk ^ (kap & 7)) << 4) + (r & 7) * 2;
    } else {
      addr = qreg + tile * 16384 + d * 128 + (((r >> 3) ^ (d & 7)) << 4) + (r & 7) * 2;
    }
    uint16_t v;
    asm volatile("ld.shared.u16 %0, [%1];" : "=h"(v) : "r"(addr));
    if (d & 1) q2[d >> 1] |= (uint32_t)v << 16; else q2[d >> 1] = v;
  }
  if (w == 0) bar_sync(NB_SLOW, 128); else bar_sync(NB_SLOW + 1, 128);
  auto score = [&](int j) {
    const uint4* kr = reinterpret_cast<const uint4*>(K + (size_t)j * 128);
    float s = 0.f;
#pragma unroll
    for (int c = 0; c < 16; c++) {
      const uint4 kv = __ldg(kr + c);
      const uint32_t kk[4] = {kv.x, kv.y, kv.z, kv.w};
#pragma unroll
      for (int e = 0; e < 4; e++) {
        s = fmaf(__uint_as_float(q2[c * 4 + e] << 16), __uint_as_float(kk[e] << 16), s);
        s = fmaf(__uint_as_float(q2[c * 4 + e] & 0xffff0000u), __uint_as_float(kk[e] & 0xffff0000u), s);
      }
    }
    return s;
  };
  if (active) {
    float m = -INFINITY;
    for (int j = 0; j < 1024; j++) {
      const float s = score(j);
      m = (s > m || s != s) ? s : m;
    }
    for (int half = 0; half < 2; half++) {
      float o[64];
#pragma unroll
      for (int i = 0; i < 64; i++) o[i] = 0.f;
      float l = 0.f;
      for (int j = 0; j < 1024; j++) {
        const float pf = exp2f(score(j) - m);
        l += pf;
        const float pr = __bfloat162float(__float2bfloat16(pf));
        const uint4* vr = reinterpret_cast<const uint4*>(V + (size_t)j * 128 + half * 64);
#pragma unroll
        for (int c = 0; c < 8; c++) {
          const uint4 vv = __ldg(vr + c);
          const uint32_t kk[4] = {vv.x, vv.y, vv.z, vv.w};
#pragma unroll
          for (int e = 0; e < 4; e++) {
            o[c * 8 + 2 * e] = fmaf(pr, __uint_as_float(kk[e] << 16), o[c * 8 + 2 * e]);
            o[c * 8 + 2 * e + 1] = fmaf(pr, __uint_as_float(kk[e] & 0xffff0000u), o[c * 8 + 2 * e + 1]);
          }
        }
      }
      const float inv = 1.f / l;
#pragma unroll
      for (int c = 0; c < 8; c++) {
        const float* x = &o[(c >> 2) * 32 + (c & 3) * 2];
        asm volatile("st.global.v4.b32 [%0], {%1, %2, %3, %4};" ::"l"(out + half * (224 * 64) + t * 64 + c * 8), "r"(pack(x[0] * inv, x[1] * inv)),
                     "r"(pack(x[8] * inv, x[9] * inv)), "r"(pack(x[16] * inv, x[17] * inv)), "r"(pack(x[24] * inv, x[25] * inv))
                     : "memory");
      }
    }
  }
}

__device__ __forceinline__ void proj_head(float (&acc)[112], uint32_t W, uint32_t sbase, bool dbg) {
  const uint32_t full0 = sbase + BAR_OFF + BAR_FULL;
  const uint32_t dbase = (sbase & 0x3FFFF) >> 4;
  const uint32_t aW = dbase + SLOT_BYTES / 16 + W * 1024, aX = dbase;
  TF(dbg, 256 + (threadIdx.x >> 5) * 8);
  mbar_wait(full0, 0);
  mbar_wait(full0 + 8, 0);
  TF(dbg, 257 + (threadIdx.x >> 5) * 8);
  wg_fence();
  mma_proj0(acc, desc(aW), desc(aX), 0);
  TF(dbg, 258 + (threadIdx.x >> 5) * 8);
#pragma unroll
  for (int ks = 1; ks < 4; ks++) mma_proj(acc, desc(aW + ks * 128), desc(aX + ks * 2), 1);
  wg_commit();
  TF(dbg, 259 + (threadIdx.x >> 5) * 8);
  mbar_wait(full0 + 16, 0);
  TF(dbg, 260 + (threadIdx.x >> 5) * 8);
  wg_fence();
#pragma unroll
  for (int ks = 0; ks < 4; ks++) mma_proj(acc, desc(aW + (4 + ks) * 128), desc(aX + 2 * (SLOT_BYTES / 16) + ks * 2), 1);
  wg_commit();
  TF(dbg, 261 + (threadIdx.x >> 5) * 8);
}
template <bool SP>
__device__ __forceinline__ void pack_o(const float (&o)[64], float i0, float i1, uint32_t (&r)[32]) {
#pragma unroll
  for (int a = 0; a < 4; a++) {
#pragma unroll
    for (int i = 0; i < 4; i++) {
      const float* x = &o[16 * a + 4 * i];
      if (SP) {
        r[8 * a + i] = pack((x[0] + x[2]) * i0, (x[1] + x[3]) * i0);
      } else {
        r[8 * a + i] = pack(x[0] * i0, x[1] * i0);
        r[8 * a + 4 + i] = pack(x[2] * i1, x[3] * i1);
      }
    }
  }
}
struct OutRegs {
  uint32_t a[32], b[32];
  char *pa, *pb;
  uint64_t pol;
  bool on, on2, sync;
};
template <int N>
__device__ __forceinline__ void store_piece(const OutRegs& o) {
  const uint32_t* r = N < 8 ? &o.a[4 * N] : &o.b[4 * (N - 8)];
  const int blk = (N & 7) >> 1;
  const int off = (blk >> 1) * (224 * 128) + (blk & 1) * 64 + (N & 1) * 1024;
  if ((N >= 8 && (N & 1)) ? o.on2 : o.on) {
    asm volatile("st.global.v4.b32 [%0], {%1, %2, %3, %4};" ::"l"((N < 8 ? o.pa : o.pb) + off), "r"(r[0]), "r"(r[1]), "r"(r[2]), "r"(r[3]) : "memory");
  }
}

struct ProjState { Cursor c; uint32_t prevX, prevW; };
template <int ST>
__device__ __forceinline__ void proj_block(float (&acc)[112], uint32_t W, ProjState& st, uint32_t rpar  , uint32_t sbase,
                                           uint32_t rel, bool rel_pred, const OutRegs& o, int dbg_kb) {
  const uint32_t full0 = sbase + BAR_OFF + BAR_FULL;
  const uint32_t dbase = (sbase & 0x3FFFF) >> 4;
  uint32_t sW, pW;
#pragma unroll
  for (int half = 0; half < 2; half++) {
    const uint32_t sX = st.c.s, pX = st.c.par ^ ((sX & 6) == 4 ? rpar : 0);
    st.c.template next<7>();
    if (half == 0) {
      sW = st.c.s;
      pW = st.c.par ^ ((sW & 6) == 4 ? rpar : 0);
      st.c.template next<7>();
    }
    const uint32_t aW = dbase + sW * (SLOT_BYTES / 16) + W * 1024;
    if (LEAD_SYNC && ST == 0 && half == 1 && W == 0 && o.sync) bar_sync(NB_LEAD, 256);
    const bool pend = true;
    if (half == 0) mbar_wait(full0 + sW * 8, pW);
    mbar_wait(full0 + sX * 8, pX);
    const uint32_t aX = dbase + sX * (SLOT_BYTES / 16);
    TF(dbg_kb >= 0 && (threadIdx.x & 127) == 0 && dbg_kb < 16, W * 64 + dbg_kb * 4 + half * 2);
    wg_fence();
#pragma unroll
    for (int ks = 0; ks < 4; ks++) mma_proj(acc, desc(aW + (half * 4 + ks) * 128), desc(aX + ks * 2), 1);
    wg_commit();
    if (ST >= 0) {
      constexpr int n0 = 8 * (ST & 1);
      if (half == 0) { store_piece<n0>(o); store_piece<n0 + 1>(o); store_piece<n0 + 2>(o); store_piece<n0 + 3>(o); }
      else { store_piece<n0 + 4>(o); store_piece<n0 + 5>(o); store_piece<n0 + 6>(o); store_piece<n0 + 7>(o); }
    }
    wg_wait<1>();
    TF(dbg_kb >= 0 && (threadIdx.x & 127) == 0 && dbg_kb < 16, W * 64 + dbg_kb * 4 + half * 2 + 1);
    if (pend && rel_pred) {
      mbar_arrive_cluster(rel + st.prevX * 8);
      if (half == 0) mbar_arrive_cluster(rel + st.prevW * 8);
    }
    if (half == 1) st.prevW = sW;
    st.prevX = sX;
  }
}
__device__ __forceinline__ void proj_rest(float (&acc)[112], uint32_t W, int round, uint32_t sbase, uint32_t rel, bool rel_pred, const OutRegs& o) {
  ProjState st{Cursor{3, 0}, 2, 1};
  const uint32_t rpar = round & 1;
  const bool dbg = round == DBG_ROUND;
  wg_wait<1>();
  if (rel_pred) mbar_arrive_cluster(rel);
  proj_block<0>(acc, W, st, rpar, sbase, rel, rel_pred, o, dbg ? 1 : -1);
  proj_block<1>(acc, W, st, rpar, sbase, rel, rel_pred, o, dbg ? 2 : -1);
  if (round > 0) mbar_arrive(sbase + BAR_OFF + BAR_OST + W * 8);
  const int nkb = round == 4 ? OPROJ_KB : 8;
#pragma unroll 1
  for (int kb = 3; kb < nkb; kb++) proj_block<-1>(acc, W, st, rpar, sbase, rel, rel_pred, o, dbg ? kb : -1);
  wg_wait<0>();
  pin(acc);
  if (rel_pred) { mbar_arrive_cluster(rel + st.prevX * 8); mbar_arrive_cluster(rel + st.prevW * 8); }
}

template <bool SP, int NT>
__device__ __forceinline__ void issue_qk(float (&s)[NT / 2], uint32_t aQ_, uint32_t aK, uint32_t meta) {
  uint32_t aQ;
  asm volatile("mov.b32 %0, %1;" : "=r"(aQ) : "r"(aQ_));
  if (SP) {
    mma_qk_sp0(s, desc(aQ), desc(aK), 0, meta);
#pragma unroll
    for (int ks = 1; ks < 4; ks++) mma_qk_sp(s, desc(aQ + ks * 128), desc(aK + (ks >> 1) * (NT * 8) + (ks & 1) * 4), 1, meta);
  } else {
    mma_qk0(s, desc(aQ), desc(aK), 0);
#pragma unroll
    for (int ks = 1; ks < 8; ks++) mma_qk(s, desc(aQ + ks * 128), desc(aK + (ks >> 2) * (NT * 8) + (ks & 3) * 2), 1);
  }
}
template <bool SP, int NT>
__device__ __forceinline__ void issue_pv(float (&o)[64], const uint32_t (&p)[24], uint32_t aV, uint32_t meta) {
  const uint32_t lo = aV | ((uint32_t)(NT * 8) << 16);
  if (SP) {
#pragma unroll
    for (int ks = 0; ks < NT / 32; ks++) mma_pv_sp(o, p[4 * ks], p[4 * ks + 1], p[4 * ks + 2], p[4 * ks + 3], desc(lo + ks * 256), 1, meta);
  } else {
#pragma unroll
    for (int ks = 0; ks < NT / 16; ks++) mma_pv(o, p[4 * ks], p[4 * ks + 1], p[4 * ks + 2], p[4 * ks + 3], desc(lo + ks * 128), 1);
  }
}
template <bool SP, int NT, int I0 = 0, int I1 = NT / 8>
__device__ __forceinline__ void exp_inplace(float (&s)[NT / 2], float& l0, float& l1) {
#pragma unroll
  for (int i = I0; i < I1; i++) {
    if (SP) {
      s[4 * i] = ex2(s[4 * i] + s[4 * i + 2]);
      s[4 * i + 1] = ex2(s[4 * i + 1] + s[4 * i + 3]);
      if (i & 1) l1 += s[4 * i] + s[4 * i + 1]; else l0 += s[4 * i] + s[4 * i + 1];
    } else {
      s[4 * i] = ex2(s[4 * i]);
      s[4 * i + 1] = ex2(s[4 * i + 1]);
      s[4 * i + 2] = ex2(s[4 * i + 2]);
      s[4 * i + 3] = ex2(s[4 * i + 3]);
      l0 += s[4 * i] + s[4 * i + 1];
      l1 += s[4 * i + 2] + s[4 * i + 3];
    }
  }
}
template <bool SP, int NT>
__device__ __forceinline__ void convert_p(const float (&s)[NT / 2], uint32_t (&p)[24]) {
  if (SP) {
    const uint32_t lane = opaque_tid() & 31;
    const bool odd = lane & 1;
    const int srcA = (lane & 28) | ((lane & 1) << 1) | ((lane >> 1) & 1);
#pragma unroll
    for (int h = 0; h < NT / 16; h++) {
      const uint32_t p0 = pack(s[8 * h], s[8 * h + 1]), p1 = pack(s[8 * h + 4], s[8 * h + 5]);
      p[2 * h] = __shfl_sync(0xffffffffu, odd ? p1 : p0, srcA);
      p[2 * h + 1] = __shfl_sync(0xffffffffu, odd ? p0 : p1, srcA ^ 1);
    }
  } else {
#pragma unroll
    for (int i = 0; i < NT / 4; i++) p[i] = pack(s[2 * i], s[2 * i + 1]);
  }
}
__device__ __forceinline__ void order_point(float a, float b, uint32_t addr, uint32_t never) {
  asm volatile("{\n.reg .pred p;\nsetp.ne.u32 p, %3, 0;\n@p st.shared.v2.f32 [%0], {%1, %2};\n}\n" ::"r"(addr), "f"(a), "f"(b), "r"(never) : "memory");
}
__device__ __forceinline__ float quad_sum(float v) {
  v += __shfl_xor_sync(0xffffffffu, v, 1);
  v += __shfl_xor_sync(0xffffffffu, v, 2);
  return v;
}
__device__ __forceinline__ bool unsafe(float l) { return !(l >= 5.9604644775390625e-08f && l <= 16777216.f); }
__device__ __forceinline__ float rcp(float x) {
  float y;
  asm("rcp.approx.ftz.f32 %0, %1;" : "=f"(y) : "f"(x));
  return y;
}

__device__ __forceinline__ __nv_bfloat16* o_tile(int round, int row) {
  return g_o + ((size_t)(((vbid() >> 3)) * 64 + (round * 8 + ((vbid() & 7))) * 2) * 224 + row) * 64;
}

template <int W>
__device__ __forceinline__ void attention(int round, uint32_t sbase, uint32_t rel, bool rel_pred, uint32_t never, uint32_t meta, float (&oB)[64],
                                          float& iB0, float& iB1, OutRegs& og) {
    constexpr bool SPB = USE_SPARSE && (W == 1);
    const uint32_t full0 = sbase + BAR_OFF + BAR_FULL;
    const uint32_t dbase = (sbase & 0x3FFFF) >> 4;
    const uint32_t aQA = dbase + (4 + W) * (SLOT_BYTES / 16), aQB = aQA + 1024;
    float oA[64];
    uint32_t pr[24];
    float lA0 = 0.f, lA1 = 0.f, lB0 = 0.f, lB1 = 0.f;
    Cursor c{3, 1};
    uint32_t sK = 3, sV;
    mbar_wait(full0 + 3 * 8, 1);
    {
      float s[32];
      if (W == 1) bar_sync(NB_ORD + 1, 256);
      wg_fence();
      issue_qk<false, 64>(s, aQA, dbase + sK * (SLOT_BYTES / 16), meta);
      wg_commit();
      bar_arrive(NB_ORD + (1 - W), 256);
#pragma unroll
      for (int i = 0; i < 64; i++) { oA[i] = 0.f; oB[i] = 0.f; }
      pin(oA);
      pin(oB);
      c.next<5>();
      sV = c.s;
      mbar_wait(full0 + sV * 8, c.par);
      wg_wait<0>();
      pin(s);
      exp_inplace<false, 64>(s, lA0, lA1);
      if (TOKEN && SPB) { order_point(lA0, lA1, sbase, never); bar_arrive(NB_TOK, 256); }
      convert_p<false, 64>(s, pr);
      mbar_wait(full0 + sV * 8, c.par);
    }
#define ORD_SYNC(k) bar_sync(NB_ORD + W, 256);
#define TI(k)
#define GROUP1(NT, NEXT)                                                    \
    {                                                                       \
      float s[NT / 2];                                                      \
      const uint32_t aV = dbase + sV * (SLOT_BYTES / 16);                   \
      TI(0)                                                                 \
      ORD_SYNC(0)                                                           \
      TI(1)                                                                 \
      wg_fence();                                                           \
      if (SPB) {                                                            \
        issue_pv<false, NT>(oA, pr, aV, meta);                              \
        issue_qk<SPB, NT>(s, aQB, dbase + sK * (SLOT_BYTES / 16), meta);    \
        wg_commit();                                                        \
        bar_arrive(NB_ORD + (1 - W), 256);                                  \
        TI(2)                                                               \
        wg_wait<0>();                                                       \
        TI(3)                                                               \
        pin(s);                                                             \
        if (rel_pred) mbar_arrive_cluster(rel + sK * 8);                    \
        exp_inplace<SPB, NT>(s, lB0, lB1);                                  \
        convert_p<SPB, NT>(s, pr);                                          \
        if (NEXT) c.next<5>();                                              \
        sK = c.s;                                                           \
        mbar_wait(full0 + sK * 8, c.par);                                   \
      } else {                                                              \
        issue_qk<SPB, NT>(s, aQB, dbase + sK * (SLOT_BYTES / 16), meta);    \
        wg_commit();                                                        \
        issue_pv<false, NT>(oA, pr, aV, meta);                              \
        wg_commit();                                                        \
        bar_arrive(NB_ORD + (1 - W), 256);                                  \
        TI(2)                                                               \
        wg_wait<1>();                                                       \
        TI(3)                                                               \
        pin(s);                                                             \
        if (rel_pred) mbar_arrive_cluster(rel + sK * 8);                    \
        if (TOKEN) { bar_sync(NB_TOK, 256); mbar_wait(full0 + sV * 8, c.par); pin(s); } \
        exp_inplace<false, NT, 0, NT * SPLIT0 / 96>(s, lB0, lB1);           \
        order_point(lB0, lB1, sbase, never);                                \
        TI(4)                                                               \
        wg_wait<0>();                                                       \
        TI(5)                                                               \
        if (NEXT) c.next<5>();                                              \
        sK = c.s;                                                           \
        mbar_wait(full0 + sK * 8, c.par);                                   \
        pin(s);                                                             \
        exp_inplace<false, NT, NT * SPLIT0 / 96, NT / 8>(s, lB0, lB1);      \
        convert_p<SPB, NT>(s, pr);                                          \
      }                                                                     \
    }
#define GROUP2(NT, NTN)                                                      \
    {                                                                       \
      float s[NTN / 2];                                                     \
      TI(6)                                                                 \
      ORD_SYNC(1)                                                           \
      TI(7)                                                                 \
      wg_fence();                                                           \
      issue_qk<false, NTN>(s, aQA, dbase + sK * (SLOT_BYTES / 16), meta);   \
      wg_commit();                                                          \
      issue_pv<SPB, NT>(oB, pr, dbase + sV * (SLOT_BYTES / 16), meta);      \
      wg_commit();                                                          \
      bar_arrive(NB_ORD + (1 - W), 256);                                    \
      TI(8)                                                                 \
      wg_wait<1>();                                                         \
      TI(9)                                                                 \
      pin(s);                                                               \
      exp_inplace<false, NTN, 0, (SPB ? SPLIT1 : SPLIT0)>(s, lA0, lA1);     \
      order_point(lA0, lA1, sbase, never);                                  \
      TI(10)                                                                \
      wg_wait<0>();                                                         \
      TI(11)                                                                \
      if (rel_pred) mbar_arrive_cluster(rel + sV * 8);                      \
      c.next<5>();                                                          \
      sV = c.s;                                                             \
      mbar_wait(full0 + sV * 8, c.par);                                     \
      pin(s);                                                               \
      exp_inplace<false, NTN, (SPB ? SPLIT1 : SPLIT0), NTN / 8>(s, lA0, lA1); \
      if (TOKEN && SPB) { order_point(lA0, lA1, sbase, never); bar_arrive(NB_TOK, 256); } \
      convert_p<false, NTN>(s, pr);                                         \
    }
    bool dbgit = false;
    GROUP1(64, true)
    mbar_wait(full0 + sK * 8, c.par);
    GROUP2(64, 96)
#pragma unroll 1
    for (int j = 0;; j++) {
      GROUP1(96, (j < 9))
      if (j == 9) break;
      GROUP2(96, 96)
    }
#undef GROUP1
#undef GROUP2
    bar_sync(NB_ORD + W, 256);
    wg_fence();
    issue_pv<SPB, 96>(oB, pr, dbase + sV * (SLOT_BYTES / 16), meta);
    wg_commit();
    if (W == 0) bar_arrive(NB_ORD + 1, 256);
    TS(4 + W * 24 + round * 4);
    TF(round == DBG_ROUND - 1, 262 + (threadIdx.x >> 5) * 8);
    lA0 = quad_sum(lA0);
    lA1 = quad_sum(lA1);
    if (SPB) { lB0 = quad_sum(lB0 + lB1); lB1 = lB0; } else { lB0 = quad_sum(lB0); lB1 = quad_sum(lB1); }
    bool bad = unsafe(lA0) || unsafe(lA1);
    bad = bad || unsafe(lB0) || unsafe(lB1);
    bad = __any_sync(0xffffffffu, bar_any(NB_VOTE + W, 128, bad));
    iB0 = rcp(lB0);
    iB1 = rcp(lB1);
    pin(oA);
    if (!bad && rel_pred) { mbar_arrive_cluster(rel + (4 + W) * 8); mbar_arrive_cluster(rel + (4 + W) * 8); }
    pack_o<false>(oA, rcp(lA0), rcp(lA1), og.a);
    {
      const uint32_t t = opaque_tid();
      const uint32_t wp = (t >> 5) & 3, g = (t >> 2) & 7, cq = t & 3;
      char* base = reinterpret_cast<char*>(o_tile(round, W * 128)) + g * 128 + cq * 16;
      og.pa = base + wp * 2048;
      og.pb = base + 8192 + wp * (SPB ? 1024 : 2048);
      og.on = !bad;
      og.on2 = !bad && !SPB;
      og.sync = true;
    }
    wg_wait<0>();
    pin(oB);
    TF(round == DBG_ROUND - 1, 263 + (threadIdx.x >> 5) * 8);
    if (rel_pred) mbar_arrive_cluster(rel + sV * 8);
    if (SPB) {
#pragma unroll
      for (int i = 0; i < 16; i++) {
        oB[4 * i] += oB[4 * i + 2];
        oB[4 * i + 1] += oB[4 * i + 3];
        oB[4 * i + 2] = oB[4 * i + 3] = 0.f;
      }
    }
}

__device__ __forceinline__ void consumer(const Params& p, uint32_t W, uint32_t sbase, uint32_t rank) {
  const uint32_t empty0 = sbase + BAR_OFF + BAR_EMPTY;
  const uint32_t tid = threadIdx.x;
  const bool rel_pred = (tid & 95) == 0;
  const uint32_t rel = mapa(empty0, ((tid >> 5) & 1) ? (rank ^ 1) : rank);
  const uint32_t qreg = sbase + 4 * SLOT_BYTES;
  const uint32_t never = p.zero;
  uint32_t meta;
  asm volatile("mov.b32 %0, %1;" : "=r"(meta) : "r"((tid & 2) ? (0x44444444u | (tid << 24 & 0x88000000u)) : 0x44EEEE44u));
  float acc[112], oB[64];
  float iB0 = 0.f, iB1 = 0.f;
  OutRegs og;
  og.on = og.on2 = og.sync = false;
  og.pa = og.pb = nullptr;
#pragma unroll
  for (int i = 0; i < 64; i++) oB[i] = 0.f;
#pragma unroll
  for (int i = 0; i < 32; i++) og.a[i] = 0;

#pragma unroll 1
  for (int round = 0;; round++) {
    TS(1 + W * 24 + round * 4);
    if (W == 0) TG(44 + round * 2);
    TF(round == DBG_ROUND && (threadIdx.x & 127) == 0, W * 64 + 0);
    proj_head(acc, W, sbase, round == DBG_ROUND);
    TF(round == DBG_ROUND && (threadIdx.x & 127) == 0, W * 64 + 2);
    if (LEAD_SYNC && W == 1 && og.sync) bar_arrive(NB_LEAD, 256);
    mbar_wait(sbase + BAR_OFF + BAR_FULL + 16, 0);
    pack_o<false>(oB, iB0, iB1, og.b);
    og.pol = round < O_EF ? 0x12F0000000000000ull : 0x1000000000000000ull;
    proj_rest(acc, W, round, sbase, rel, rel_pred, og);
    TS(2 + W * 24 + round * 4);
    if (round == 4) break;
    {
      mbar_wait(empty0 + 4 * 8, 0);
      mbar_wait(empty0 + 5 * 8, 0);
      const float sc = 0.12751743f;
      const uint32_t t = opaque_tid();
      const uint32_t lane = t & 31, wp = (t >> 5) & 3, mi = lane >> 3, r7 = lane & 7;
      const uint32_t dd = 64 * W + 16 * wp + 8 * (mi & 1) + r7;
      const uint32_t rowa = qreg + dd * 128;
#pragma unroll
      for (int i = 0; i < 28; i += 2) {
        uint32_t addr;
        if (USE_SPARSE && i >= 24) {
          const uint32_t kap = 16 * (dd >> 5) + 2 * ((dd & 31) >> 2) + (dd & 1), h = ((dd >> 1) ^ (dd >> 3)) & 1;
          const uint32_t chunk = 2 * (i - 24 + (mi >> 1)) + h;
          addr = qreg + 3 * 16384 + kap * 128 + ((chunk ^ (kap & 7)) << 4);
        } else {
          addr = rowa + (i >> 3) * 16384 + ((((i & 7) + (mi >> 1)) ^ r7) << 4);
        }
        stsm4(addr, pack(acc[4 * i] * sc, acc[4 * i + 1] * sc), pack(acc[4 * i + 2] * sc, acc[4 * i + 3] * sc),
              pack(acc[4 * i + 4] * sc, acc[4 * i + 5] * sc), pack(acc[4 * i + 6] * sc, acc[4 * i + 7] * sc));
      }
      fence_async_smem();
      bar_sync(NB_QREADY, 256);
      TS(3 + W * 24 + round * 4);
      if (W == 0) TG(45 + round * 2);
    }
    if (W == 0) attention<0>(round, sbase, rel, rel_pred, never, meta, oB, iB0, iB1, og);
    else attention<1>(round, sbase, rel, rel_pred, never, meta, oB, iB0, iB1, og);
    if (!og.on) {
      const int pair = (vbid() >> 3), head = round * 8 + ((vbid() & 7));
      const size_t off = (size_t)((pair & 7) * 32 + head) * (1024 * 128);
      slow_rows(qreg + W * SLOT_BYTES, W, p.kp[pair >> 3] + off, p.vp[pair >> 3] + off, o_tile(round, W * 128));
      if (rel_pred) { mbar_arrive_cluster(rel + (4 + W) * 8); mbar_arrive_cluster(rel + (4 + W) * 8); }
#pragma unroll
      for (int i = 0; i < 64; i++) oB[i] = 0.f;
#pragma unroll
      for (int i = 0; i < 32; i++) og.a[i] = 0;
    }
  }
  {
    if (W == 0) TG(53);
    cluster_arrive();
    mbar_wait(empty0 + (5 + W) * 8, 0);
    const uint32_t t = opaque_tid();
    const uint32_t lane = t & 31, wp = (t >> 5) & 3, mi = lane >> 3, r7 = lane & 7;
    const uint32_t base = sbase + (5 + W) * SLOT_BYTES + (8 * (mi >> 1) + r7) * 128 + (((2 * wp + (mi & 1)) ^ r7) << 4);
#pragma unroll
    for (int i = 0; i < 28; i += 2)
      stsm4t(base + i * 1024, pack(acc[4 * i], acc[4 * i + 1]), pack(acc[4 * i + 2], acc[4 * i + 3]),
             pack(acc[4 * i + 4], acc[4 * i + 5]), pack(acc[4 * i + 6], acc[4 * i + 7]));
    fence_async_smem();
    mbar_arrive(sbase + BAR_OFF + BAR_OST + W * 8);
  }
}

template <int SEL>
__device__ __forceinline__ void loader(const Params& p, uint32_t sbase, uint32_t rank) {
  const uint32_t full0 = sbase + BAR_OFF + BAR_FULL, empty0 = sbase + BAR_OFF + BAR_EMPTY;
  const int pair = (vbid() >> 3), cc = (vbid() & 7), br = pair >> 3, b = pair & 7;
  const uint64_t pol = KV_POL;
  const uint32_t lane = threadIdx.x & 31;
  if (PF_C && elect_one()) {
    if (SEL == 0) {
      tma_prefetch(&p.wq[br], cc * 128, b * 128);
      tma_prefetch(&p.wq[br], cc * 128 + 64, b * 128);
    } else {
#pragma unroll
      for (int i = 0; i < 4; i++) tma_prefetch(&p.x[br], cc * 128 + (i & 1) * 64, b * 224 + (i >> 1) * 112);
    }
  }
#pragma unroll 1
  for (int round = 0; round < 5; round++) {
    const bool oproj = round == 4;
    const int head = round * 8 + cc;
    const int kvrow = (b * 32 + head) * 1024;
    const char* pfp = reinterpret_cast<const char*>(SEL ? p.vp[br] : p.kp[br]) + (size_t)kvrow * 256 + lane * 128;
    const char* pfu = reinterpret_cast<const char*>(SEL ? p.vp[br] : p.kp[br]) + (size_t)kvrow * 256;
    int pf = oproj ? 64 : PF_SKIP;
    auto prefetch = [&](int n) {
      if (PF_ENABLE == 1) {
#pragma unroll
        for (int i = 0; i < n; i++) {
          if (pf < 64) { asm volatile("prefetch.global.L2 [%0];" ::"l"(pfp + pf * 4096)); pf++; }
        }
      } else if (PF_ENABLE == 3) {
#pragma unroll
        for (int i = 0; i < n; i += 2) {
          if (pf < 64) {
            uint32_t v;
            asm volatile("ld.global.L1::no_allocate.L2::cache_hint.L2::256B.b32 %0, [%1], %2;" : "=r"(v) : "l"(pfu + pf * 4096 + lane * 256), "l"((uint64_t)PF_POL));
            pf += 2;
          }
        }
      } else if (PF_ENABLE == 2) {
        if (pf < 64) {
          const int cnt = min(n, 64 - pf);
          if (elect_one())
            asm volatile("cp.async.bulk.prefetch.L2.global.L2::cache_hint [%0], %1, %2;" ::"l"(pfu + pf * 4096), "r"(cnt * 4096), "l"((uint64_t)PF_POL) : "memory");
          pf += cnt;
        }
      }
    };
    auto oprefetch = [&](int kb) {
      if (SEL == 0) {
        if ((kb & 7) == b && kb < 32 && elect_one()) {
          tma_prefetch(&p.wo[br], cc * 128, kb * 128);
          tma_prefetch(&p.wo[br], cc * 128 + 64, kb * 128);
        }
      } else if ((kb & 3) == (cc >> 1) && kb < 24) {
        mbar_wait(sbase + BAR_OFF + BAR_FLAG + (kb >> 3) * 8, 0);
        if (elect_one()) {
          tma_prefetch(&p.o_ld, 0, (pair * 64 + kb * 2) * 224 + rank * 112);
          tma_prefetch(&p.o_ld, 0, (pair * 64 + kb * 2 + 1) * 224 + rank * 112);
        }
      }
    };
    const CUtensorMap* m = SEL ? (oproj ? &p.o_ld : &p.x[br]) : (oproj ? &p.wo5[br] : &p.wq[br]);
    const int fixed = SEL ? (oproj ? pair * 64 : b) * 224 + rank * 112 : (oproj ? cc : head) * 128;
    const int nkb = oproj ? OPROJ_KB : 8;
    Cursor c{0, 1};
#pragma unroll 1
    for (int kb = 0; kb < nkb; kb++) {
      if (SEL == 0) {
        c.next<7>();
        mbar_wait(empty0 + c.s * 8, c.par);
        TF(round == DBG_ROUND && kb < 16, 128 + kb * 3 + 1);
        if (elect_one()) {
          const uint32_t dst = sbase + c.s * SLOT_BYTES, bar = full0 + c.s * 8;
          mbar_expect_tx(bar, 32768);
          if (oproj) {
            tma_load5(dst, m, fixed, KBW * 4, bar);
            tma_load5(dst + 16384, m, fixed + 64, KBW * 4, bar);
          } else {
            tma_load(dst, m, fixed, KBW * 128, bar);
            tma_load(dst + 16384, m, fixed + 64, KBW * 128, bar);
          }
        }
        c.next<7>(); c.next<7>();
        if (kb >= PF_G0) prefetch(PF_G);
      } else {
        if (oproj && (kb & 7) == 0) {
          mbar_wait(sbase + BAR_OFF + BAR_FLAG + (kb >> 3) * 8, 0);
          asm volatile("fence.proxy.async.global;" ::: "memory");
        }
#pragma unroll
        for (int half = 0; half < 2; half++) {
          mbar_wait(empty0 + c.s * 8, c.par);
          TF(round == DBG_ROUND && kb < 16, 128 + kb * 3 + 2 * half);
          if (elect_one()) {
            mbar_expect_tx(full0 + c.s * 8, 28672);
            tma_load_mc(sbase + c.s * SLOT_BYTES + rank * 14336, m, oproj ? 0 : kb * 128 + half * 64,
                        oproj ? fixed + (KBX * 2 + half) * 224 : fixed, full0 + c.s * 8);
          }
          c.next<7>();
          if (half == 0) c.next<7>();
        }
        if (kb >= PF_G0) prefetch(PF_G);
      }
      if (PF_O && oproj) {
        if (kb == 0) for (int i = PF_O0; i < PF_O; i++) oprefetch(i);
        oprefetch(kb + PF_O);
      }
    }
    if (oproj) break;
    c = Cursor{SEL ? 6u : 3u, 0};
#pragma unroll 1
    for (int j = 0; j < 11; j++) {
      mbar_wait(empty0 + c.s * 8, c.par);
      if (elect_one()) {
        const uint32_t half = j == 0 ? 8192 : 12288;
        const int row = kvrow + (j == 0 ? 0 : j * 96 - 32);
        const uint32_t dst = sbase + c.s * SLOT_BYTES, bar = full0 + c.s * 8;
        const CUtensorMap* mk = &p.kv[br][SEL][j == 0];
        mbar_expect_tx(bar, 2 * half);
        tma_load_hint(dst, mk, 0, row, bar, pol);
        tma_load_hint(dst + half, mk, 64, row, bar, pol);
      }
      c.next<5>(); c.next<5>();
      prefetch(PF_A);
      if (round < 3) {
        if (PF_X && SEL == 1 && (j == PF_X || j == PF_X2)) {
          const char* xp = reinterpret_cast<const char*>(p.xp[br]) + (size_t)(b * 224 + cc * 28) * 2048 + lane * 128;
#pragma unroll
          for (int i = 0; i < 14; i++) asm volatile("prefetch.global.L2 [%0];" ::"l"(xp + i * 4096));
        }
        if (PF_W && SEL == 0 && j == PF_WJ) {
          if (PF_W == 1) {
            if (elect_one()) {
              tma_prefetch(&p.wq[br], (head + 8) * 128, b * 128);
              tma_prefetch(&p.wq[br], (head + 8) * 128 + 64, b * 128);
            }
          } else {
            const char* wp = reinterpret_cast<const char*>(p.wqp[br]) + (size_t)(b * 128 + (lane >> 1)) * 8192 + (head + 8) * 256 + (lane & 1) * 128;
#pragma unroll
            for (int i = 0; i < 8; i++) asm volatile("prefetch.global.L2 [%0];" ::"l"(wp + i * 16 * 8192));
          }
        }
      } else if (j >= 11 - PF_O0) {
        oprefetch(j - (11 - PF_O0));
      }
    }
  }
}

__device__ __forceinline__ void storer(const Params& p, uint32_t sbase) {
  const uint32_t ost = sbase + BAR_OFF + BAR_OST;
  const int pair = (vbid() >> 3), cc = (vbid() & 7);
#pragma unroll 1
  for (int round = 0; round < 4; round++) {
    mbar_wait(ost, round & 1);
    mbar_wait(ost + 8, round & 1);
    if (elect_one()) {
      __threadfence();
      asm volatile("red.release.gpu.global.add.u32 [%0], 1;" ::"l"(&g_flags[pair * 4 + round]) : "memory");
    }
    __syncwarp();
  }
  cluster_arrive();
#pragma unroll
  for (int w = 0; w < 2; w++) {
    mbar_wait(ost + w * 8, 0);
    if (elect_one()) tma_store(&p.out_st, (pair >> 3) * 1024 + cc * 128 + w * 64, (pair & 7) * 224, sbase + (5 + w) * SLOT_BYTES);
  }
  if (elect_one()) {
    asm volatile("cp.async.bulk.commit_group;" ::: "memory");
    asm volatile("cp.async.bulk.wait_group.read 0;" ::: "memory");
  }
  __syncwarp();
}

__device__ __forceinline__ void watcher(uint32_t sbase) {
  if (elect_one()) {
    const unsigned epoch = g_epoch[blockIdx.x];
    const unsigned target = (epoch + 1) * 8;
#pragma unroll 1
    for (int r = 0; r < 4; r++) {
      const unsigned* f = &g_flags[((vbid() >> 3)) * 4 + r];
      uint32_t n = 0;
      while (true) {
        unsigned v;
        asm volatile("ld.acquire.gpu.global.u32 %0, [%1];" : "=r"(v) : "l"(f) : "memory");
        if ((int)(v - target) >= 0) break;
        if (++n > SPIN_LIMIT) __trap();
        __nanosleep(500);
      }
      mbar_arrive(sbase + BAR_OFF + BAR_FLAG + r * 8);
    }
    g_epoch[blockIdx.x] = epoch + 1;
  }
}

__global__ void __cluster_dims__(2, 1, 1) __launch_bounds__(384, 1) fused_kernel(const __grid_constant__ Params p) {
  extern __shared__ uint8_t smem_raw[];
  const uint32_t sbase = (smem_u32(smem_raw) + 1023) & ~1023u;
  uint32_t rank;
  asm("mov.u32 %0, %%cluster_ctarank;" : "=r"(rank));
  const int wid = __shfl_sync(0xffffffffu, threadIdx.x >> 5, 0);
  if (threadIdx.x == 0) { TS(0); TG(60); }
  if (wid == 8 && elect_one()) {
    for (int i = 0; i < NSLOT; i++) {
      mbar_init(sbase + BAR_OFF + BAR_FULL + i * 8, 1);
      mbar_init(sbase + BAR_OFF + BAR_EMPTY + i * 8, 4);
    }
    mbar_init(sbase + BAR_OFF + BAR_OST, 128);
    mbar_init(sbase + BAR_OFF + BAR_OST + 8, 128);
    for (int i = 0; i < 4; i++) mbar_init(sbase + BAR_OFF + BAR_FLAG + i * 8, 1);
    asm volatile("fence.mbarrier_init.release.cluster;" ::: "memory");
  } else if (wid == 9 && elect_one()) {
    const int br = (vbid() >> 6);
    asm volatile("prefetch.tensormap [%0];" ::"l"(&p.x[br]) : "memory");
    asm volatile("prefetch.tensormap [%0];" ::"l"(&p.wq[br]) : "memory");
    asm volatile("prefetch.tensormap [%0];" ::"l"(&p.kv[br][0][1]) : "memory");
    asm volatile("prefetch.tensormap [%0];" ::"l"(&p.kv[br][1][1]) : "memory");
  }
  __syncwarp();
  cluster_arrive();
  cluster_wait();
  if (wid >= 8) {
    asm volatile("setmaxnreg.dec.sync.aligned.u32 %0;" ::"n"(PREGS));
    if (wid == 10) {
      storer(p, sbase);
    } else {
      if (wid == 8) loader<0>(p, sbase, rank);
      else if (wid == 9) loader<1>(p, sbase, rank);
      else watcher(sbase);
      __syncwarp();
      cluster_arrive();
    }
    cluster_wait();
  } else {
    asm volatile("setmaxnreg.inc.sync.aligned.u32 %0;" ::"n"(CREGS));
    consumer(p, wid >> 2, sbase, rank);
    cluster_wait();
    if (threadIdx.x == 0) { TS(19); TG(61); }
  }
}

typedef CUresult (*EncodeFn)(CUtensorMap*, CUtensorMapDataType, cuuint32_t, void*, const cuuint64_t*, const cuuint64_t*,
                             const cuuint32_t*, const cuuint32_t*, CUtensorMapInterleave, CUtensorMapSwizzle,
                             CUtensorMapL2promotion, CUtensorMapFloatOOBfill);

void make_map(EncodeFn enc, CUtensorMap* m, const void* ptr, uint64_t cols, uint64_t rows, uint32_t box_rows) {
  cuuint64_t dims[2] = {cols, rows};
  cuuint64_t strides[1] = {cols * 2};
  cuuint32_t box[2] = {64, box_rows};
  cuuint32_t es[2] = {1, 1};
  enc(m, CU_TENSOR_MAP_DATA_TYPE_BFLOAT16, 2, const_cast<void*>(ptr), dims, strides, box, es, CU_TENSOR_MAP_INTERLEAVE_NONE,
      CU_TENSOR_MAP_SWIZZLE_128B, CU_TENSOR_MAP_L2_PROMOTION_L2_256B, CU_TENSOR_MAP_FLOAT_OOB_FILL_NONE);
}

}

extern "C" void kernel_launch(void* const* d_in, const int* in_sizes, int n_in, void* d_out, int out_size) {
  static EncodeFn enc = nullptr;
  static void* o_ptr = nullptr;
  if (!enc) {
    cudaDriverEntryPointQueryResult qr;
    cudaGetDriverEntryPoint("cuTensorMapEncodeTiled", (void**)&enc, cudaEnableDefault, &qr);
    cudaGetSymbolAddress(&o_ptr, g_o);
    cudaFuncSetAttribute(fused_kernel, cudaFuncAttributeMaxDynamicSharedMemorySize, SMEM_TOTAL);
  }
  Params p;
  for (int br = 0; br < 2; br++) {
    make_map(enc, &p.x[br], d_in[br * 5 + 0], 1024, 1792, 112);
    for (int t = 0; t < 2; t++) {
      make_map(enc, &p.kv[br][t][0], d_in[br * 5 + 1 + t], 128, 262144, 96);
      make_map(enc, &p.kv[br][t][1], d_in[br * 5 + 1 + t], 128, 262144, 64);
    }
    make_map(enc, &p.wq[br], d_in[br * 5 + 3], 4096, 1024, 128);
    make_map(enc, &p.wo[br], d_in[br * 5 + 4], 1024, 4096, 128);
    {
      cuuint64_t dims[5] = {1024, 2, 4, 4, 128};
      cuuint64_t strides[4] = {2048, 8 * 2048, 2 * 2048, 32 * 2048};
      cuuint32_t box[5] = {64, 2, 4, 4, 4};
      cuuint32_t es[5] = {1, 1, 1, 1, 1};
      enc(&p.wo5[br], CU_TENSOR_MAP_DATA_TYPE_BFLOAT16, 5, d_in[br * 5 + 4], dims, strides, box, es, CU_TENSOR_MAP_INTERLEAVE_NONE,
          CU_TENSOR_MAP_SWIZZLE_128B, CU_TENSOR_MAP_L2_PROMOTION_L2_256B, CU_TENSOR_MAP_FLOAT_OOB_FILL_NONE);
    }
    p.kp[br] = (const __nv_bfloat16*)d_in[br * 5 + 1];
    p.vp[br] = (const __nv_bfloat16*)d_in[br * 5 + 2];
    p.wqp[br] = (const __nv_bfloat16*)d_in[br * 5 + 3];
    p.wop[br] = (const __nv_bfloat16*)d_in[br * 5 + 4];
    p.xp[br] = (const __nv_bfloat16*)d_in[br * 5 + 0];
  }
  p.zero = 0;
  make_map(enc, &p.o_ld, o_ptr, 64, 16 * 64 * 224, 112);
  make_map(enc, &p.out_st, d_out, 2048, 1792, 224);
  fused_kernel<<<128, 384, SMEM_TOTAL>>>(p);
}
```

```cpp
#include <cuda_runtime.h>
#include <cuda_bf16.h>
#include <cuda.h>
#include <stdint.h>

namespace {

constexpr int SLOT_BYTES = 32768;
constexpr int SLOT_D = SLOT_BYTES / 16;
constexpr int NSLOT = 7;
constexpr int BAR_OFF = NSLOT * SLOT_BYTES;
constexpr int SMEM_TOTAL = BAR_OFF + 256 + 1024;
constexpr uint32_t BAR_FULL = 0, BAR_EMPTY = 64, BAR_OST = 128, BAR_FLAG = 144, BAR_OST2 = 176;
constexpr uint32_t SPIN_LIMIT = 1u << 24;
constexpr int NB_QREADY = 1, NB_ORD = 2  , NB_VOTE = 4  , NB_SLOW = 6  , NB_LEAD = 8, NB_Q1 = 9;
constexpr uint64_t POL_NORMAL = 0x1000000000000000ull, POL_FIRST = 0x12F0000000000000ull;

struct alignas(64) Params {
  CUtensorMap x[2], wq[2], kv[2][2][2]  , wo[2], o_ld, out_st;
  CUtensorMap wo64, o24, o88, out24, out88;
  const __nv_bfloat16* kp[2];
  const __nv_bfloat16* vp[2];
  uint32_t zero, helpers;
};

__device__ __nv_bfloat16 g_o[2 * 1792 * 4096];
__device__ unsigned g_flags[64];
__device__ unsigned g_epoch[132];

__device__ __forceinline__ void mma_proj(float (&d)[112], uint64_t da, uint64_t db, int acc) {
  asm volatile("{\n.reg .pred p;\n"
    "setp.ne.b32 p, %114, 0;\n"
    "wgmma.mma_async.sync.aligned.m64n224k16.f32.bf16.bf16 {%0, %1, %2, %3, %4, %5, %6, %7, %8, %9, %10, %11, %12, %13, %14, %15, %16, %17, %18, %19, %20, %21, %22, %23, %24, %25, %26, %27, %28, %29, %30, %31, %32, %33, %34, %35, %36, %37, %38, %39, %40, %41, %42, %43, %44, %45, %46, %47, %48, %49, %50, %51, %52, %53, %54, %55, %56, %57, %58, %59, %60, %61, %62, %63, %64, %65, %66, %67, %68, %69, %70, %71, %72, %73, %74, %75, %76, %77, %78, %79, %80, %81, %82, %83, %84, %85, %86, %87, %88, %89, %90, %91, %92, %93, %94, %95, %96, %97, %98, %99, %100, %101, %102, %103, %104, %105, %106, %107, %108, %109, %110, %111}, %112, %113, p, 1, 1, 1, 0;\n}\n"
    : "+f"(d[0]), "+f"(d[1]), "+f"(d[2]), "+f"(d[3]), "+f"(d[4]), "+f"(d[5]), "+f"(d[6]), "+f"(d[7]), "+f"(d[8]), "+f"(d[9]), "+f"(d[10]), "+f"(d[11]), "+f"(d[12]), "+f"(d[13]), "+f"(d[14]), "+f"(d[15]), "+f"(d[16]), "+f"(d[17]), "+f"(d[18]), "+f"(d[19]), "+f"(d[20]), "+f"(d[21]), "+f"(d[22]), "+f"(d[23]), "+f"(d[24]), "+f"(d[25]), "+f"(d[26]), "+f"(d[27]), "+f"(d[28]), "+f"(d[29]), "+f"(d[30]), "+f"(d[31]), "+f"(d[32]), "+f"(d[33]), "+f"(d[34]), "+f"(d[35]), "+f"(d[36]), "+f"(d[37]), "+f"(d[38]), "+f"(d[39]), "+f"(d[40]), "+f"(d[41]), "+f"(d[42]), "+f"(d[43]), "+f"(d[44]), "+f"(d[45]), "+f"(d[46]), "+f"(d[47]), "+f"(d[48]), "+f"(d[49]), "+f"(d[50]), "+f"(d[51]), "+f"(d[52]), "+f"(d[53]), "+f"(d[54]), "+f"(d[55]), "+f"(d[56]), "+f"(d[57]), "+f"(d[58]), "+f"(d[59]), "+f"(d[60]), "+f"(d[61]), "+f"(d[62]), "+f"(d[63]), "+f"(d[64]), "+f"(d[65]), "+f"(d[66]), "+f"(d[67]), "+f"(d[68]), "+f"(d[69]), "+f"(d[70]), "+f"(d[71]), "+f"(d[72]), "+f"(d[73]), "+f"(d[74]), "+f"(d[75]), "+f"(d[76]), "+f"(d[77]), "+f"(d[78]), "+f"(d[79]), "+f"(d[80]), "+f"(d[81]), "+f"(d[82]), "+f"(d[83]), "+f"(d[84]), "+f"(d[85]), "+f"(d[86]), "+f"(d[87]), "+f"(d[88]), "+f"(d[89]), "+f"(d[90]), "+f"(d[91]), "+f"(d[92]), "+f"(d[93]), "+f"(d[94]), "+f"(d[95]), "+f"(d[96]), "+f"(d[97]), "+f"(d[98]), "+f"(d[99]), "+f"(d[100]), "+f"(d[101]), "+f"(d[102]), "+f"(d[103]), "+f"(d[104]), "+f"(d[105]), "+f"(d[106]), "+f"(d[107]), "+f"(d[108]), "+f"(d[109]), "+f"(d[110]), "+f"(d[111])
    : "l"(da), "l"(db), "r"(acc));
}
__device__ __forceinline__ void mma_proj0(float (&d)[112], uint64_t da, uint64_t db, int acc) {
  asm volatile("{\n.reg .pred p;\n"
    "setp.ne.b32 p, %114, 0;\n"
    "wgmma.mma_async.sync.aligned.m64n224k16.f32.bf16.bf16 {%0, %1, %2, %3, %4, %5, %6, %7, %8, %9, %10, %11, %12, %13, %14, %15, %16, %17, %18, %19, %20, %21, %22, %23, %24, %25, %26, %27, %28, %29, %30, %31, %32, %33, %34, %35, %36, %37, %38, %39, %40, %41, %42, %43, %44, %45, %46, %47, %48, %49, %50, %51, %52, %53, %54, %55, %56, %57, %58, %59, %60, %61, %62, %63, %64, %65, %66, %67, %68, %69, %70, %71, %72, %73, %74, %75, %76, %77, %78, %79, %80, %81, %82, %83, %84, %85, %86, %87, %88, %89, %90, %91, %92, %93, %94, %95, %96, %97, %98, %99, %100, %101, %102, %103, %104, %105, %106, %107, %108, %109, %110, %111}, %112, %113, p, 1, 1, 1, 0;\n}\n"
    : "=f"(d[0]), "=f"(d[1]), "=f"(d[2]), "=f"(d[3]), "=f"(d[4]), "=f"(d[5]), "=f"(d[6]), "=f"(d[7]), "=f"(d[8]), "=f"(d[9]), "=f"(d[10]), "=f"(d[11]), "=f"(d[12]), "=f"(d[13]), "=f"(d[14]), "=f"(d[15]), "=f"(d[16]), "=f"(d[17]), "=f"(d[18]), "=f"(d[19]), "=f"(d[20]), "=f"(d[21]), "=f"(d[22]), "=f"(d[23]), "=f"(d[24]), "=f"(d[25]), "=f"(d[26]), "=f"(d[27]), "=f"(d[28]), "=f"(d[29]), "=f"(d[30]), "=f"(d[31]), "=f"(d[32]), "=f"(d[33]), "=f"(d[34]), "=f"(d[35]), "=f"(d[36]), "=f"(d[37]), "=f"(d[38]), "=f"(d[39]), "=f"(d[40]), "=f"(d[41]), "=f"(d[42]), "=f"(d[43]), "=f"(d[44]), "=f"(d[45]), "=f"(d[46]), "=f"(d[47]), "=f"(d[48]), "=f"(d[49]), "=f"(d[50]), "=f"(d[51]), "=f"(d[52]), "=f"(d[53]), "=f"(d[54]), "=f"(d[55]), "=f"(d[56]), "=f"(d[57]), "=f"(d[58]), "=f"(d[59]), "=f"(d[60]), "=f"(d[61]), "=f"(d[62]), "=f"(d[63]), "=f"(d[64]), "=f"(d[65]), "=f"(d[66]), "=f"(d[67]), "=f"(d[68]), "=f"(d[69]), "=f"(d[70]), "=f"(d[71]), "=f"(d[72]), "=f"(d[73]), "=f"(d[74]), "=f"(d[75]), "=f"(d[76]), "=f"(d[77]), "=f"(d[78]), "=f"(d[79]), "=f"(d[80]), "=f"(d[81]), "=f"(d[82]), "=f"(d[83]), "=f"(d[84]), "=f"(d[85]), "=f"(d[86]), "=f"(d[87]), "=f"(d[88]), "=f"(d[89]), "=f"(d[90]), "=f"(d[91]), "=f"(d[92]), "=f"(d[93]), "=f"(d[94]), "=f"(d[95]), "=f"(d[96]), "=f"(d[97]), "=f"(d[98]), "=f"(d[99]), "=f"(d[100]), "=f"(d[101]), "=f"(d[102]), "=f"(d[103]), "=f"(d[104]), "=f"(d[105]), "=f"(d[106]), "=f"(d[107]), "=f"(d[108]), "=f"(d[109]), "=f"(d[110]), "=f"(d[111])
    : "l"(da), "l"(db), "r"(acc));
}
__device__ __forceinline__ void mma_proj(float (&d)[100], uint64_t da, uint64_t db, int acc) {
  asm volatile("{\n.reg .pred p;\n"
    "setp.ne.b32 p, %102, 0;\n"
    "wgmma.mma_async.sync.aligned.m64n200k16.f32.bf16.bf16 {%0, %1, %2, %3, %4, %5, %6, %7, %8, %9, %10, %11, %12, %13, %14, %15, %16, %17, %18, %19, %20, %21, %22, %23, %24, %25, %26, %27, %28, %29, %30, %31, %32, %33, %34, %35, %36, %37, %38, %39, %40, %41, %42, %43, %44, %45, %46, %47, %48, %49, %50, %51, %52, %53, %54, %55, %56, %57, %58, %59, %60, %61, %62, %63, %64, %65, %66, %67, %68, %69, %70, %71, %72, %73, %74, %75, %76, %77, %78, %79, %80, %81, %82, %83, %84, %85, %86, %87, %88, %89, %90, %91, %92, %93, %94, %95, %96, %97, %98, %99}, %100, %101, p, 1, 1, 1, 0;\n}\n"
    : "+f"(d[0]), "+f"(d[1]), "+f"(d[2]), "+f"(d[3]), "+f"(d[4]), "+f"(d[5]), "+f"(d[6]), "+f"(d[7]), "+f"(d[8]), "+f"(d[9]), "+f"(d[10]), "+f"(d[11]), "+f"(d[12]), "+f"(d[13]), "+f"(d[14]), "+f"(d[15]), "+f"(d[16]), "+f"(d[17]), "+f"(d[18]), "+f"(d[19]), "+f"(d[20]), "+f"(d[21]), "+f"(d[22]), "+f"(d[23]), "+f"(d[24]), "+f"(d[25]), "+f"(d[26]), "+f"(d[27]), "+f"(d[28]), "+f"(d[29]), "+f"(d[30]), "+f"(d[31]), "+f"(d[32]), "+f"(d[33]), "+f"(d[34]), "+f"(d[35]), "+f"(d[36]), "+f"(d[37]), "+f"(d[38]), "+f"(d[39]), "+f"(d[40]), "+f"(d[41]), "+f"(d[42]), "+f"(d[43]), "+f"(d[44]), "+f"(d[45]), "+f"(d[46]), "+f"(d[47]), "+f"(d[48]), "+f"(d[49]), "+f"(d[50]), "+f"(d[51]), "+f"(d[52]), "+f"(d[53]), "+f"(d[54]), "+f"(d[55]), "+f"(d[56]), "+f"(d[57]), "+f"(d[58]), "+f"(d[59]), "+f"(d[60]), "+f"(d[61]), "+f"(d[62]), "+f"(d[63]), "+f"(d[64]), "+f"(d[65]), "+f"(d[66]), "+f"(d[67]), "+f"(d[68]), "+f"(d[69]), "+f"(d[70]), "+f"(d[71]), "+f"(d[72]), "+f"(d[73]), "+f"(d[74]), "+f"(d[75]), "+f"(d[76]), "+f"(d[77]), "+f"(d[78]), "+f"(d[79]), "+f"(d[80]), "+f"(d[81]), "+f"(d[82]), "+f"(d[83]), "+f"(d[84]), "+f"(d[85]), "+f"(d[86]), "+f"(d[87]), "+f"(d[88]), "+f"(d[89]), "+f"(d[90]), "+f"(d[91]), "+f"(d[92]), "+f"(d[93]), "+f"(d[94]), "+f"(d[95]), "+f"(d[96]), "+f"(d[97]), "+f"(d[98]), "+f"(d[99])
    : "l"(da), "l"(db), "r"(acc));
}
__device__ __forceinline__ void mma_proj0(float (&d)[100], uint64_t da, uint64_t db, int acc) {
  asm volatile("{\n.reg .pred p;\n"
    "setp.ne.b32 p, %102, 0;\n"
    "wgmma.mma_async.sync.aligned.m64n200k16.f32.bf16.bf16 {%0, %1, %2, %3, %4, %5, %6, %7, %8, %9, %10, %11, %12, %13, %14, %15, %16, %17, %18, %19, %20, %21, %22, %23, %24, %25, %26, %27, %28, %29, %30, %31, %32, %33, %34, %35, %36, %37, %38, %39, %40, %41, %42, %43, %44, %45, %46, %47, %48, %49, %50, %51, %52, %53, %54, %55, %56, %57, %58, %59, %60, %61, %62, %63, %64, %65, %66, %67, %68, %69, %70, %71, %72, %73, %74, %75, %76, %77, %78, %79, %80, %81, %82, %83, %84, %85, %86, %87, %88, %89, %90, %91, %92, %93, %94, %95, %96, %97, %98, %99}, %100, %101, p, 1, 1, 1, 0;\n}\n"
    : "=f"(d[0]), "=f"(d[1]), "=f"(d[2]), "=f"(d[3]), "=f"(d[4]), "=f"(d[5]), "=f"(d[6]), "=f"(d[7]), "=f"(d[8]), "=f"(d[9]), "=f"(d[10]), "=f"(d[11]), "=f"(d[12]), "=f"(d[13]), "=f"(d[14]), "=f"(d[15]), "=f"(d[16]), "=f"(d[17]), "=f"(d[18]), "=f"(d[19]), "=f"(d[20]), "=f"(d[21]), "=f"(d[22]), "=f"(d[23]), "=f"(d[24]), "=f"(d[25]), "=f"(d[26]), "=f"(d[27]), "=f"(d[28]), "=f"(d[29]), "=f"(d[30]), "=f"(d[31]), "=f"(d[32]), "=f"(d[33]), "=f"(d[34]), "=f"(d[35]), "=f"(d[36]), "=f"(d[37]), "=f"(d[38]), "=f"(d[39]), "=f"(d[40]), "=f"(d[41]), "=f"(d[42]), "=f"(d[43]), "=f"(d[44]), "=f"(d[45]), "=f"(d[46]), "=f"(d[47]), "=f"(d[48]), "=f"(d[49]), "=f"(d[50]), "=f"(d[51]), "=f"(d[52]), "=f"(d[53]), "=f"(d[54]), "=f"(d[55]), "=f"(d[56]), "=f"(d[57]), "=f"(d[58]), "=f"(d[59]), "=f"(d[60]), "=f"(d[61]), "=f"(d[62]), "=f"(d[63]), "=f"(d[64]), "=f"(d[65]), "=f"(d[66]), "=f"(d[67]), "=f"(d[68]), "=f"(d[69]), "=f"(d[70]), "=f"(d[71]), "=f"(d[72]), "=f"(d[73]), "=f"(d[74]), "=f"(d[75]), "=f"(d[76]), "=f"(d[77]), "=f"(d[78]), "=f"(d[79]), "=f"(d[80]), "=f"(d[81]), "=f"(d[82]), "=f"(d[83]), "=f"(d[84]), "=f"(d[85]), "=f"(d[86]), "=f"(d[87]), "=f"(d[88]), "=f"(d[89]), "=f"(d[90]), "=f"(d[91]), "=f"(d[92]), "=f"(d[93]), "=f"(d[94]), "=f"(d[95]), "=f"(d[96]), "=f"(d[97]), "=f"(d[98]), "=f"(d[99])
    : "l"(da), "l"(db), "r"(acc));
}
__device__ __forceinline__ void mma_proj(float (&d)[96], uint64_t da, uint64_t db, int acc) {
  asm volatile("{\n.reg .pred p;\n"
    "setp.ne.b32 p, %98, 0;\n"
    "wgmma.mma_async.sync.aligned.m64n192k16.f32.bf16.bf16 {%0, %1, %2, %3, %4, %5, %6, %7, %8, %9, %10, %11, %12, %13, %14, %15, %16, %17, %18, %19, %20, %21, %22, %23, %24, %25, %26, %27, %28, %29, %30, %31, %32, %33, %34, %35, %36, %37, %38, %39, %40, %41, %42, %43, %44, %45, %46, %47, %48, %49, %50, %51, %52, %53, %54, %55, %56, %57, %58, %59, %60, %61, %62, %63, %64, %65, %66, %67, %68, %69, %70, %71, %72, %73, %74, %75, %76, %77, %78, %79, %80, %81, %82, %83, %84, %85, %86, %87, %88, %89, %90, %91, %92, %93, %94, %95}, %96, %97, p, 1, 1, 1, 0;\n}\n"
    : "+f"(d[0]), "+f"(d[1]), "+f"(d[2]), "+f"(d[3]), "+f"(d[4]), "+f"(d[5]), "+f"(d[6]), "+f"(d[7]), "+f"(d[8]), "+f"(d[9]), "+f"(d[10]), "+f"(d[11]), "+f"(d[12]), "+f"(d[13]), "+f"(d[14]), "+f"(d[15]), "+f"(d[16]), "+f"(d[17]), "+f"(d[18]), "+f"(d[19]), "+f"(d[20]), "+f"(d[21]), "+f"(d[22]), "+f"(d[23]), "+f"(d[24]), "+f"(d[25]), "+f"(d[26]), "+f"(d[27]), "+f"(d[28]), "+f"(d[29]), "+f"(d[30]), "+f"(d[31]), "+f"(d[32]), "+f"(d[33]), "+f"(d[34]), "+f"(d[35]), "+f"(d[36]), "+f"(d[37]), "+f"(d[38]), "+f"(d[39]), "+f"(d[40]), "+f"(d[41]), "+f"(d[42]), "+f"(d[43]), "+f"(d[44]), "+f"(d[45]), "+f"(d[46]), "+f"(d[47]), "+f"(d[48]), "+f"(d[49]), "+f"(d[50]), "+f"(d[51]), "+f"(d[52]), "+f"(d[53]), "+f"(d[54]), "+f"(d[55]), "+f"(d[56]), "+f"(d[57]), "+f"(d[58]), "+f"(d[59]), "+f"(d[60]), "+f"(d[61]), "+f"(d[62]), "+f"(d[63]), "+f"(d[64]), "+f"(d[65]), "+f"(d[66]), "+f"(d[67]), "+f"(d[68]), "+f"(d[69]), "+f"(d[70]), "+f"(d[71]), "+f"(d[72]), "+f"(d[73]), "+f"(d[74]), "+f"(d[75]), "+f"(d[76]), "+f"(d[77]), "+f"(d[78]), "+f"(d[79]), "+f"(d[80]), "+f"(d[81]), "+f"(d[82]), "+f"(d[83]), "+f"(d[84]), "+f"(d[85]), "+f"(d[86]), "+f"(d[87]), "+f"(d[88]), "+f"(d[89]), "+f"(d[90]), "+f"(d[91]), "+f"(d[92]), "+f"(d[93]), "+f"(d[94]), "+f"(d[95])
    : "l"(da), "l"(db), "r"(acc));
}
__device__ __forceinline__ void mma_pv0(float (&d)[64], uint32_t a0, uint32_t a1, uint32_t a2, uint32_t a3, uint64_t db, int acc) {
  asm volatile("{\n.reg .pred p;\n"
    "setp.ne.b32 p, %69, 0;\n"
    "wgmma.mma_async.sync.aligned.m64n128k16.f32.bf16.bf16 {%0, %1, %2, %3, %4, %5, %6, %7, %8, %9, %10, %11, %12, %13, %14, %15, %16, %17, %18, %19, %20, %21, %22, %23, %24, %25, %26, %27, %28, %29, %30, %31, %32, %33, %34, %35, %36, %37, %38, %39, %40, %41, %42, %43, %44, %45, %46, %47, %48, %49, %50, %51, %52, %53, %54, %55, %56, %57, %58, %59, %60, %61, %62, %63}, {%64, %65, %66, %67}, %68, p, 1, 1, 1;\n}\n"
    : "=f"(d[0]), "=f"(d[1]), "=f"(d[2]), "=f"(d[3]), "=f"(d[4]), "=f"(d[5]), "=f"(d[6]), "=f"(d[7]), "=f"(d[8]), "=f"(d[9]), "=f"(d[10]), "=f"(d[11]), "=f"(d[12]), "=f"(d[13]), "=f"(d[14]), "=f"(d[15]), "=f"(d[16]), "=f"(d[17]), "=f"(d[18]), "=f"(d[19]), "=f"(d[20]), "=f"(d[21]), "=f"(d[22]), "=f"(d[23]), "=f"(d[24]), "=f"(d[25]), "=f"(d[26]), "=f"(d[27]), "=f"(d[28]), "=f"(d[29]), "=f"(d[30]), "=f"(d[31]), "=f"(d[32]), "=f"(d[33]), "=f"(d[34]), "=f"(d[35]), "=f"(d[36]), "=f"(d[37]), "=f"(d[38]), "=f"(d[39]), "=f"(d[40]), "=f"(d[41]), "=f"(d[42]), "=f"(d[43]), "=f"(d[44]), "=f"(d[45]), "=f"(d[46]), "=f"(d[47]), "=f"(d[48]), "=f"(d[49]), "=f"(d[50]), "=f"(d[51]), "=f"(d[52]), "=f"(d[53]), "=f"(d[54]), "=f"(d[55]), "=f"(d[56]), "=f"(d[57]), "=f"(d[58]), "=f"(d[59]), "=f"(d[60]), "=f"(d[61]), "=f"(d[62]), "=f"(d[63])
    : "r"(a0), "r"(a1), "r"(a2), "r"(a3), "l"(db), "r"(acc));
}
__device__ __forceinline__ void mma_pv_sp0(float (&d)[64], uint32_t a0, uint32_t a1, uint32_t a2, uint32_t a3, uint64_t db, int acc, uint32_t meta) {
  asm volatile("{\n.reg .pred p;\n"
    "setp.ne.b32 p, %69, 0;\n"
    "wgmma.mma_async.sp.sync.aligned.m64n128k32.f32.bf16.bf16 {%0, %1, %2, %3, %4, %5, %6, %7, %8, %9, %10, %11, %12, %13, %14, %15, %16, %17, %18, %19, %20, %21, %22, %23, %24, %25, %26, %27, %28, %29, %30, %31, %32, %33, %34, %35, %36, %37, %38, %39, %40, %41, %42, %43, %44, %45, %46, %47, %48, %49, %50, %51, %52, %53, %54, %55, %56, %57, %58, %59, %60, %61, %62, %63}, {%64, %65, %66, %67}, %68, %70, 0, p, 1, 1, 1;\n}\n"
    : "=f"(d[0]), "=f"(d[1]), "=f"(d[2]), "=f"(d[3]), "=f"(d[4]), "=f"(d[5]), "=f"(d[6]), "=f"(d[7]), "=f"(d[8]), "=f"(d[9]), "=f"(d[10]), "=f"(d[11]), "=f"(d[12]), "=f"(d[13]), "=f"(d[14]), "=f"(d[15]), "=f"(d[16]), "=f"(d[17]), "=f"(d[18]), "=f"(d[19]), "=f"(d[20]), "=f"(d[21]), "=f"(d[22]), "=f"(d[23]), "=f"(d[24]), "=f"(d[25]), "=f"(d[26]), "=f"(d[27]), "=f"(d[28]), "=f"(d[29]), "=f"(d[30]), "=f"(d[31]), "=f"(d[32]), "=f"(d[33]), "=f"(d[34]), "=f"(d[35]), "=f"(d[36]), "=f"(d[37]), "=f"(d[38]), "=f"(d[39]), "=f"(d[40]), "=f"(d[41]), "=f"(d[42]), "=f"(d[43]), "=f"(d[44]), "=f"(d[45]), "=f"(d[46]), "=f"(d[47]), "=f"(d[48]), "=f"(d[49]), "=f"(d[50]), "=f"(d[51]), "=f"(d[52]), "=f"(d[53]), "=f"(d[54]), "=f"(d[55]), "=f"(d[56]), "=f"(d[57]), "=f"(d[58]), "=f"(d[59]), "=f"(d[60]), "=f"(d[61]), "=f"(d[62]), "=f"(d[63])
    : "r"(a0), "r"(a1), "r"(a2), "r"(a3), "l"(db), "r"(acc), "r"(meta));
}
__device__ __forceinline__ void mma_qk(float (&d)[48], uint64_t da, uint64_t db, int acc) {
  asm volatile("{\n.reg .pred p;\n"
    "setp.ne.b32 p, %50, 0;\n"
    "wgmma.mma_async.sync.aligned.m64n96k16.f32.bf16.bf16 {%0, %1, %2, %3, %4, %5, %6, %7, %8, %9, %10, %11, %12, %13, %14, %15, %16, %17, %18, %19, %20, %21, %22, %23, %24, %25, %26, %27, %28, %29, %30, %31, %32, %33, %34, %35, %36, %37, %38, %39, %40, %41, %42, %43, %44, %45, %46, %47}, %48, %49, p, 1, 1, 1, 0;\n}\n"
    : "+f"(d[0]), "+f"(d[1]), "+f"(d[2]), "+f"(d[3]), "+f"(d[4]), "+f"(d[5]), "+f"(d[6]), "+f"(d[7]), "+f"(d[8]), "+f"(d[9]), "+f"(d[10]), "+f"(d[11]), "+f"(d[12]), "+f"(d[13]), "+f"(d[14]), "+f"(d[15]), "+f"(d[16]), "+f"(d[17]), "+f"(d[18]), "+f"(d[19]), "+f"(d[20]), "+f"(d[21]), "+f"(d[22]), "+f"(d[23]), "+f"(d[24]), "+f"(d[25]), "+f"(d[26]), "+f"(d[27]), "+f"(d[28]), "+f"(d[29]), "+f"(d[30]), "+f"(d[31]), "+f"(d[32]), "+f"(d[33]), "+f"(d[34]), "+f"(d[35]), "+f"(d[36]), "+f"(d[37]), "+f"(d[38]), "+f"(d[39]), "+f"(d[40]), "+f"(d[41]), "+f"(d[42]), "+f"(d[43]), "+f"(d[44]), "+f"(d[45]), "+f"(d[46]), "+f"(d[47])
    : "l"(da), "l"(db), "r"(acc));
}
__device__ __forceinline__ void mma_qk0(float (&d)[48], uint64_t da, uint64_t db, int acc) {
  asm volatile("{\n.reg .pred p;\n"
    "setp.ne.b32 p, %50, 0;\n"
    "wgmma.mma_async.sync.aligned.m64n96k16.f32.bf16.bf16 {%0, %1, %2, %3, %4, %5, %6, %7, %8, %9, %10, %11, %12, %13, %14, %15, %16, %17, %18, %19, %20, %21, %22, %23, %24, %25, %26, %27, %28, %29, %30, %31, %32, %33, %34, %35, %36, %37, %38, %39, %40, %41, %42, %43, %44, %45, %46, %47}, %48, %49, p, 1, 1, 1, 0;\n}\n"
    : "=f"(d[0]), "=f"(d[1]), "=f"(d[2]), "=f"(d[3]), "=f"(d[4]), "=f"(d[5]), "=f"(d[6]), "=f"(d[7]), "=f"(d[8]), "=f"(d[9]), "=f"(d[10]), "=f"(d[11]), "=f"(d[12]), "=f"(d[13]), "=f"(d[14]), "=f"(d[15]), "=f"(d[16]), "=f"(d[17]), "=f"(d[18]), "=f"(d[19]), "=f"(d[20]), "=f"(d[21]), "=f"(d[22]), "=f"(d[23]), "=f"(d[24]), "=f"(d[25]), "=f"(d[26]), "=f"(d[27]), "=f"(d[28]), "=f"(d[29]), "=f"(d[30]), "=f"(d[31]), "=f"(d[32]), "=f"(d[33]), "=f"(d[34]), "=f"(d[35]), "=f"(d[36]), "=f"(d[37]), "=f"(d[38]), "=f"(d[39]), "=f"(d[40]), "=f"(d[41]), "=f"(d[42]), "=f"(d[43]), "=f"(d[44]), "=f"(d[45]), "=f"(d[46]), "=f"(d[47])
    : "l"(da), "l"(db), "r"(acc));
}
__device__ __forceinline__ void mma_qk_sp(float (&d)[48], uint64_t da, uint64_t db, int acc, uint32_t meta) {
  asm volatile("{\n.reg .pred p;\n"
    "setp.ne.b32 p, %50, 0;\n"
    "wgmma.mma_async.sp.sync.aligned.m64n96k32.f32.bf16.bf16 {%0, %1, %2, %3, %4, %5, %6, %7, %8, %9, %10, %11, %12, %13, %14, %15, %16, %17, %18, %19, %20, %21, %22, %23, %24, %25, %26, %27, %28, %29, %30, %31, %32, %33, %34, %35, %36, %37, %38, %39, %40, %41, %42, %43, %44, %45, %46, %47}, %48, %49, %51, 0, p, 1, 1, 1, 0;\n}\n"
    : "+f"(d[0]), "+f"(d[1]), "+f"(d[2]), "+f"(d[3]), "+f"(d[4]), "+f"(d[5]), "+f"(d[6]), "+f"(d[7]), "+f"(d[8]), "+f"(d[9]), "+f"(d[10]), "+f"(d[11]), "+f"(d[12]), "+f"(d[13]), "+f"(d[14]), "+f"(d[15]), "+f"(d[16]), "+f"(d[17]), "+f"(d[18]), "+f"(d[19]), "+f"(d[20]), "+f"(d[21]), "+f"(d[22]), "+f"(d[23]), "+f"(d[24]), "+f"(d[25]), "+f"(d[26]), "+f"(d[27]), "+f"(d[28]), "+f"(d[29]), "+f"(d[30]), "+f"(d[31]), "+f"(d[32]), "+f"(d[33]), "+f"(d[34]), "+f"(d[35]), "+f"(d[36]), "+f"(d[37]), "+f"(d[38]), "+f"(d[39]), "+f"(d[40]), "+f"(d[41]), "+f"(d[42]), "+f"(d[43]), "+f"(d[44]), "+f"(d[45]), "+f"(d[46]), "+f"(d[47])
    : "l"(da), "l"(db), "r"(acc), "r"(meta));
}
__device__ __forceinline__ void mma_qk_sp0(float (&d)[48], uint64_t da, uint64_t db, int acc, uint32_t meta) {
  asm volatile("{\n.reg .pred p;\n"
    "setp.ne.b32 p, %50, 0;\n"
    "wgmma.mma_async.sp.sync.aligned.m64n96k32.f32.bf16.bf16 {%0, %1, %2, %3, %4, %5, %6, %7, %8, %9, %10, %11, %12, %13, %14, %15, %16, %17, %18, %19, %20, %21, %22, %23, %24, %25, %26, %27, %28, %29, %30, %31, %32, %33, %34, %35, %36, %37, %38, %39, %40, %41, %42, %43, %44, %45, %46, %47}, %48, %49, %51, 0, p, 1, 1, 1, 0;\n}\n"
    : "=f"(d[0]), "=f"(d[1]), "=f"(d[2]), "=f"(d[3]), "=f"(d[4]), "=f"(d[5]), "=f"(d[6]), "=f"(d[7]), "=f"(d[8]), "=f"(d[9]), "=f"(d[10]), "=f"(d[11]), "=f"(d[12]), "=f"(d[13]), "=f"(d[14]), "=f"(d[15]), "=f"(d[16]), "=f"(d[17]), "=f"(d[18]), "=f"(d[19]), "=f"(d[20]), "=f"(d[21]), "=f"(d[22]), "=f"(d[23]), "=f"(d[24]), "=f"(d[25]), "=f"(d[26]), "=f"(d[27]), "=f"(d[28]), "=f"(d[29]), "=f"(d[30]), "=f"(d[31]), "=f"(d[32]), "=f"(d[33]), "=f"(d[34]), "=f"(d[35]), "=f"(d[36]), "=f"(d[37]), "=f"(d[38]), "=f"(d[39]), "=f"(d[40]), "=f"(d[41]), "=f"(d[42]), "=f"(d[43]), "=f"(d[44]), "=f"(d[45]), "=f"(d[46]), "=f"(d[47])
    : "l"(da), "l"(db), "r"(acc), "r"(meta));
}
__device__ __forceinline__ void mma_qk_spr(float (&d)[48], uint32_t a0, uint32_t a1, uint32_t a2, uint32_t a3, uint64_t db, int acc, uint32_t meta) {
  asm volatile("{\n.reg .pred p;\n"
    "setp.ne.b32 p, %53, 0;\n"
    "wgmma.mma_async.sp.sync.aligned.m64n96k32.f32.bf16.bf16 {%0, %1, %2, %3, %4, %5, %6, %7, %8, %9, %10, %11, %12, %13, %14, %15, %16, %17, %18, %19, %20, %21, %22, %23, %24, %25, %26, %27, %28, %29, %30, %31, %32, %33, %34, %35, %36, %37, %38, %39, %40, %41, %42, %43, %44, %45, %46, %47}, {%48, %49, %50, %51}, %52, %54, 0, p, 1, 1, 0;\n}\n"
    : "+f"(d[0]), "+f"(d[1]), "+f"(d[2]), "+f"(d[3]), "+f"(d[4]), "+f"(d[5]), "+f"(d[6]), "+f"(d[7]), "+f"(d[8]), "+f"(d[9]), "+f"(d[10]), "+f"(d[11]), "+f"(d[12]), "+f"(d[13]), "+f"(d[14]), "+f"(d[15]), "+f"(d[16]), "+f"(d[17]), "+f"(d[18]), "+f"(d[19]), "+f"(d[20]), "+f"(d[21]), "+f"(d[22]), "+f"(d[23]), "+f"(d[24]), "+f"(d[25]), "+f"(d[26]), "+f"(d[27]), "+f"(d[28]), "+f"(d[29]), "+f"(d[30]), "+f"(d[31]), "+f"(d[32]), "+f"(d[33]), "+f"(d[34]), "+f"(d[35]), "+f"(d[36]), "+f"(d[37]), "+f"(d[38]), "+f"(d[39]), "+f"(d[40]), "+f"(d[41]), "+f"(d[42]), "+f"(d[43]), "+f"(d[44]), "+f"(d[45]), "+f"(d[46]), "+f"(d[47])
    : "r"(a0), "r"(a1), "r"(a2), "r"(a3), "l"(db), "r"(acc), "r"(meta));
}
__device__ __forceinline__ void mma_qk(float (&d)[32], uint64_t da, uint64_t db, int acc) {
  asm volatile("{\n.reg .pred p;\n"
    "setp.ne.b32 p, %34, 0;\n"
    "wgmma.mma_async.sync.aligned.m64n64k16.f32.bf16.bf16 {%0, %1, %2, %3, %4, %5, %6, %7, %8, %9, %10, %11, %12, %13, %14, %15, %16, %17, %18, %19, %20, %21, %22, %23, %24, %25, %26, %27, %28, %29, %30, %31}, %32, %33, p, 1, 1, 1, 0;\n}\n"
    : "+f"(d[0]), "+f"(d[1]), "+f"(d[2]), "+f"(d[3]), "+f"(d[4]), "+f"(d[5]), "+f"(d[6]), "+f"(d[7]), "+f"(d[8]), "+f"(d[9]), "+f"(d[10]), "+f"(d[11]), "+f"(d[12]), "+f"(d[13]), "+f"(d[14]), "+f"(d[15]), "+f"(d[16]), "+f"(d[17]), "+f"(d[18]), "+f"(d[19]), "+f"(d[20]), "+f"(d[21]), "+f"(d[22]), "+f"(d[23]), "+f"(d[24]), "+f"(d[25]), "+f"(d[26]), "+f"(d[27]), "+f"(d[28]), "+f"(d[29]), "+f"(d[30]), "+f"(d[31])
    : "l"(da), "l"(db), "r"(acc));
}
__device__ __forceinline__ void mma_qk0(float (&d)[32], uint64_t da, uint64_t db, int acc) {
  asm volatile("{\n.reg .pred p;\n"
    "setp.ne.b32 p, %34, 0;\n"
    "wgmma.mma_async.sync.aligned.m64n64k16.f32.bf16.bf16 {%0, %1, %2, %3, %4, %5, %6, %7, %8, %9, %10, %11, %12, %13, %14, %15, %16, %17, %18, %19, %20, %21, %22, %23, %24, %25, %26, %27, %28, %29, %30, %31}, %32, %33, p, 1, 1, 1, 0;\n}\n"
    : "=f"(d[0]), "=f"(d[1]), "=f"(d[2]), "=f"(d[3]), "=f"(d[4]), "=f"(d[5]), "=f"(d[6]), "=f"(d[7]), "=f"(d[8]), "=f"(d[9]), "=f"(d[10]), "=f"(d[11]), "=f"(d[12]), "=f"(d[13]), "=f"(d[14]), "=f"(d[15]), "=f"(d[16]), "=f"(d[17]), "=f"(d[18]), "=f"(d[19]), "=f"(d[20]), "=f"(d[21]), "=f"(d[22]), "=f"(d[23]), "=f"(d[24]), "=f"(d[25]), "=f"(d[26]), "=f"(d[27]), "=f"(d[28]), "=f"(d[29]), "=f"(d[30]), "=f"(d[31])
    : "l"(da), "l"(db), "r"(acc));
}
__device__ __forceinline__ void mma_qk_sp(float (&d)[32], uint64_t da, uint64_t db, int acc, uint32_t meta) {
  asm volatile("{\n.reg .pred p;\n"
    "setp.ne.b32 p, %34, 0;\n"
    "wgmma.mma_async.sp.sync.aligned.m64n64k32.f32.bf16.bf16 {%0, %1, %2, %3, %4, %5, %6, %7, %8, %9, %10, %11, %12, %13, %14, %15, %16, %17, %18, %19, %20, %21, %22, %23, %24, %25, %26, %27, %28, %29, %30, %31}, %32, %33, %35, 0, p, 1, 1, 1, 0;\n}\n"
    : "+f"(d[0]), "+f"(d[1]), "+f"(d[2]), "+f"(d[3]), "+f"(d[4]), "+f"(d[5]), "+f"(d[6]), "+f"(d[7]), "+f"(d[8]), "+f"(d[9]), "+f"(d[10]), "+f"(d[11]), "+f"(d[12]), "+f"(d[13]), "+f"(d[14]), "+f"(d[15]), "+f"(d[16]), "+f"(d[17]), "+f"(d[18]), "+f"(d[19]), "+f"(d[20]), "+f"(d[21]), "+f"(d[22]), "+f"(d[23]), "+f"(d[24]), "+f"(d[25]), "+f"(d[26]), "+f"(d[27]), "+f"(d[28]), "+f"(d[29]), "+f"(d[30]), "+f"(d[31])
    : "l"(da), "l"(db), "r"(acc), "r"(meta));
}
__device__ __forceinline__ void mma_qk_sp0(float (&d)[32], uint64_t da, uint64_t db, int acc, uint32_t meta) {
  asm volatile("{\n.reg .pred p;\n"
    "setp.ne.b32 p, %34, 0;\n"
    "wgmma.mma_async.sp.sync.aligned.m64n64k32.f32.bf16.bf16 {%0, %1, %2, %3, %4, %5, %6, %7, %8, %9, %10, %11, %12, %13, %14, %15, %16, %17, %18, %19, %20, %21, %22, %23, %24, %25, %26, %27, %28, %29, %30, %31}, %32, %33, %35, 0, p, 1, 1, 1, 0;\n}\n"
    : "=f"(d[0]), "=f"(d[1]), "=f"(d[2]), "=f"(d[3]), "=f"(d[4]), "=f"(d[5]), "=f"(d[6]), "=f"(d[7]), "=f"(d[8]), "=f"(d[9]), "=f"(d[10]), "=f"(d[11]), "=f"(d[12]), "=f"(d[13]), "=f"(d[14]), "=f"(d[15]), "=f"(d[16]), "=f"(d[17]), "=f"(d[18]), "=f"(d[19]), "=f"(d[20]), "=f"(d[21]), "=f"(d[22]), "=f"(d[23]), "=f"(d[24]), "=f"(d[25]), "=f"(d[26]), "=f"(d[27]), "=f"(d[28]), "=f"(d[29]), "=f"(d[30]), "=f"(d[31])
    : "l"(da), "l"(db), "r"(acc), "r"(meta));
}
__device__ __forceinline__ void mma_qk_spr(float (&d)[32], uint32_t a0, uint32_t a1, uint32_t a2, uint32_t a3, uint64_t db, int acc, uint32_t meta) {
  asm volatile("{\n.reg .pred p;\n"
    "setp.ne.b32 p, %37, 0;\n"
    "wgmma.mma_async.sp.sync.aligned.m64n64k32.f32.bf16.bf16 {%0, %1, %2, %3, %4, %5, %6, %7, %8, %9, %10, %11, %12, %13, %14, %15, %16, %17, %18, %19, %20, %21, %22, %23, %24, %25, %26, %27, %28, %29, %30, %31}, {%32, %33, %34, %35}, %36, %38, 0, p, 1, 1, 0;\n}\n"
    : "+f"(d[0]), "+f"(d[1]), "+f"(d[2]), "+f"(d[3]), "+f"(d[4]), "+f"(d[5]), "+f"(d[6]), "+f"(d[7]), "+f"(d[8]), "+f"(d[9]), "+f"(d[10]), "+f"(d[11]), "+f"(d[12]), "+f"(d[13]), "+f"(d[14]), "+f"(d[15]), "+f"(d[16]), "+f"(d[17]), "+f"(d[18]), "+f"(d[19]), "+f"(d[20]), "+f"(d[21]), "+f"(d[22]), "+f"(d[23]), "+f"(d[24]), "+f"(d[25]), "+f"(d[26]), "+f"(d[27]), "+f"(d[28]), "+f"(d[29]), "+f"(d[30]), "+f"(d[31])
    : "r"(a0), "r"(a1), "r"(a2), "r"(a3), "l"(db), "r"(acc), "r"(meta));
}
__device__ __forceinline__ void mma_pv(float (&d)[64], uint32_t a0, uint32_t a1, uint32_t a2, uint32_t a3, uint64_t db, int acc) {
  asm volatile("{\n.reg .pred p;\n"
    "setp.ne.b32 p, %69, 0;\n"
    "wgmma.mma_async.sync.aligned.m64n128k16.f32.bf16.bf16 {%0, %1, %2, %3, %4, %5, %6, %7, %8, %9, %10, %11, %12, %13, %14, %15, %16, %17, %18, %19, %20, %21, %22, %23, %24, %25, %26, %27, %28, %29, %30, %31, %32, %33, %34, %35, %36, %37, %38, %39, %40, %41, %42, %43, %44, %45, %46, %47, %48, %49, %50, %51, %52, %53, %54, %55, %56, %57, %58, %59, %60, %61, %62, %63}, {%64, %65, %66, %67}, %68, p, 1, 1, 1;\n}\n"
    : "+f"(d[0]), "+f"(d[1]), "+f"(d[2]), "+f"(d[3]), "+f"(d[4]), "+f"(d[5]), "+f"(d[6]), "+f"(d[7]), "+f"(d[8]), "+f"(d[9]), "+f"(d[10]), "+f"(d[11]), "+f"(d[12]), "+f"(d[13]), "+f"(d[14]), "+f"(d[15]), "+f"(d[16]), "+f"(d[17]), "+f"(d[18]), "+f"(d[19]), "+f"(d[20]), "+f"(d[21]), "+f"(d[22]), "+f"(d[23]), "+f"(d[24]), "+f"(d[25]), "+f"(d[26]), "+f"(d[27]), "+f"(d[28]), "+f"(d[29]), "+f"(d[30]), "+f"(d[31]), "+f"(d[32]), "+f"(d[33]), "+f"(d[34]), "+f"(d[35]), "+f"(d[36]), "+f"(d[37]), "+f"(d[38]), "+f"(d[39]), "+f"(d[40]), "+f"(d[41]), "+f"(d[42]), "+f"(d[43]), "+f"(d[44]), "+f"(d[45]), "+f"(d[46]), "+f"(d[47]), "+f"(d[48]), "+f"(d[49]), "+f"(d[50]), "+f"(d[51]), "+f"(d[52]), "+f"(d[53]), "+f"(d[54]), "+f"(d[55]), "+f"(d[56]), "+f"(d[57]), "+f"(d[58]), "+f"(d[59]), "+f"(d[60]), "+f"(d[61]), "+f"(d[62]), "+f"(d[63])
    : "r"(a0), "r"(a1), "r"(a2), "r"(a3), "l"(db), "r"(acc));
}
__device__ __forceinline__ void mma_pv_sp(float (&d)[64], uint32_t a0, uint32_t a1, uint32_t a2, uint32_t a3, uint64_t db, int acc, uint32_t meta) {
  asm volatile("{\n.reg .pred p;\n"
    "setp.ne.b32 p, %69, 0;\n"
    "wgmma.mma_async.sp.sync.aligned.m64n128k32.f32.bf16.bf16 {%0, %1, %2, %3, %4, %5, %6, %7, %8, %9, %10, %11, %12, %13, %14, %15, %16, %17, %18, %19, %20, %21, %22, %23, %24, %25, %26, %27, %28, %29, %30, %31, %32, %33, %34, %35, %36, %37, %38, %39, %40, %41, %42, %43, %44, %45, %46, %47, %48, %49, %50, %51, %52, %53, %54, %55, %56, %57, %58, %59, %60, %61, %62, %63}, {%64, %65, %66, %67}, %68, %70, 0, p, 1, 1, 1;\n}\n"
    : "+f"(d[0]), "+f"(d[1]), "+f"(d[2]), "+f"(d[3]), "+f"(d[4]), "+f"(d[5]), "+f"(d[6]), "+f"(d[7]), "+f"(d[8]), "+f"(d[9]), "+f"(d[10]), "+f"(d[11]), "+f"(d[12]), "+f"(d[13]), "+f"(d[14]), "+f"(d[15]), "+f"(d[16]), "+f"(d[17]), "+f"(d[18]), "+f"(d[19]), "+f"(d[20]), "+f"(d[21]), "+f"(d[22]), "+f"(d[23]), "+f"(d[24]), "+f"(d[25]), "+f"(d[26]), "+f"(d[27]), "+f"(d[28]), "+f"(d[29]), "+f"(d[30]), "+f"(d[31]), "+f"(d[32]), "+f"(d[33]), "+f"(d[34]), "+f"(d[35]), "+f"(d[36]), "+f"(d[37]), "+f"(d[38]), "+f"(d[39]), "+f"(d[40]), "+f"(d[41]), "+f"(d[42]), "+f"(d[43]), "+f"(d[44]), "+f"(d[45]), "+f"(d[46]), "+f"(d[47]), "+f"(d[48]), "+f"(d[49]), "+f"(d[50]), "+f"(d[51]), "+f"(d[52]), "+f"(d[53]), "+f"(d[54]), "+f"(d[55]), "+f"(d[56]), "+f"(d[57]), "+f"(d[58]), "+f"(d[59]), "+f"(d[60]), "+f"(d[61]), "+f"(d[62]), "+f"(d[63])
    : "r"(a0), "r"(a1), "r"(a2), "r"(a3), "l"(db), "r"(acc), "r"(meta));
}

__device__ __forceinline__ void wg_fence() { asm volatile("wgmma.fence.sync.aligned;" ::: "memory"); }
__device__ __forceinline__ void wg_commit() { asm volatile("wgmma.commit_group.sync.aligned;" ::: "memory"); }
template <int N> __device__ __forceinline__ void wg_wait() { asm volatile("wgmma.wait_group.sync.aligned %0;" ::"n"(N) : "memory"); }
template <int N> __device__ __forceinline__ void pin(float (&d)[N]) {
#pragma unroll
  for (int i = 0; i < N; i++) asm volatile("" : "+f"(d[i])::"memory");
}
__device__ __forceinline__ uint64_t desc(uint32_t lo) { return ((uint64_t)0x40000040u << 32) | lo; }
__device__ __forceinline__ uint64_t desc2(uint32_t lo) { return ((uint64_t)0x40000080u << 32) | lo; }
__device__ __forceinline__ void mbar_init(uint32_t bar, int cnt) { asm volatile("mbarrier.init.shared::cta.b64 [%0], %1;" ::"r"(bar), "r"(cnt) : "memory"); }
__device__ __forceinline__ void mbar_expect_tx(uint32_t bar, uint32_t bytes) {
  asm volatile("mbarrier.arrive.expect_tx.shared::cta.b64 _, [%0], %1;" ::"r"(bar), "r"(bytes) : "memory");
}
__device__ __forceinline__ void mbar_wait(uint32_t bar, uint32_t parity) {
  asm volatile(
      "{\n.reg .pred p;\n.reg .u32 n;\n"
      "mbarrier.try_wait.parity.shared::cta.b64 p, [%0], %1;\n"
      "@p bra DONE;\n"
      "mov.u32 n, 0;\n"
      "SPIN:\n"
      "mbarrier.try_wait.parity.shared::cta.b64 p, [%0], %1;\n"
      "@p bra DONE;\n"
      "add.u32 n, n, 1;\n"
      "setp.lt.u32 p, n, %2;\n"
      "@p bra SPIN;\n"
      "trap;\n"
      "DONE:\n}\n" ::"r"(bar), "r"(parity), "n"(SPIN_LIMIT) : "memory");
}
__device__ __forceinline__ void mbar_wait_soft(uint32_t bar, uint32_t parity) {
  asm volatile(
      "{\n.reg .pred p;\n.reg .u32 n;\n"
      "mov.u32 n, 0;\n"
      "SPIN:\n"
      "mbarrier.try_wait.parity.shared::cta.b64 p, [%0], %1, 250;\n"
      "@p bra DONE;\n"
      "add.u32 n, n, 1;\n"
      "setp.lt.u32 p, n, 32;\n"
      "@p bra SPIN;\n"
      "DONE:\n}\n" ::"r"(bar), "r"(parity) : "memory");
}
__device__ __forceinline__ void mbar_arrive(uint32_t bar) { asm volatile("mbarrier.arrive.shared::cta.b64 _, [%0];" ::"r"(bar) : "memory"); }
__device__ __forceinline__ void mbar_arrive_cluster(uint32_t addr) { asm volatile("mbarrier.arrive.shared::cluster.b64 _, [%0];" ::"r"(addr) : "memory"); }
__device__ __forceinline__ void release(uint32_t addr, bool on) {
  asm volatile("{\n.reg .pred p;\nsetp.ne.u32 p, %1, 0;\n@p mbarrier.arrive.shared::cluster.b64 _, [%0];\n}\n" ::"r"(addr), "r"((uint32_t)on) : "memory");
}
__device__ __forceinline__ uint32_t mapa(uint32_t addr, uint32_t rank) {
  uint32_t r;
  asm("mapa.shared::cluster.u32 %0, %1, %2;" : "=r"(r) : "r"(addr), "r"(rank));
  return r;
}
__device__ __forceinline__ void tma_load2(uint32_t dst, const CUtensorMap* m, int c0, int c1, uint32_t bar) {
  asm volatile("cp.async.bulk.tensor.2d.shared::cluster.global.mbarrier::complete_tx::bytes [%0], [%1, {%3, %4}], [%2];"
               ::"r"(dst), "l"(m), "r"(bar), "r"(c0), "r"(c1) : "memory");
}
__device__ __forceinline__ void tma_load4(uint32_t dst, const CUtensorMap* m, int c3, uint32_t bar, uint64_t pol) {
  asm volatile("cp.async.bulk.tensor.4d.shared::cluster.global.mbarrier::complete_tx::bytes.L2::cache_hint [%0], [%1, {%4, %4, %4, %3}], [%2], %5;"
               ::"r"(dst), "l"(m), "r"(bar), "r"(c3), "r"(0), "l"(pol) : "memory");
}
__device__ __forceinline__ void tma_load5(uint32_t dst, const CUtensorMap* m, int c0, int c4, uint32_t bar) {
  asm volatile("cp.async.bulk.tensor.5d.shared::cluster.global.mbarrier::complete_tx::bytes [%0], [%1, {%3, %5, %5, %5, %4}], [%2];"
               ::"r"(dst), "l"(m), "r"(bar), "r"(c0), "r"(c4), "r"(0) : "memory");
}
__device__ __forceinline__ void tma_load_mc(uint32_t dst, const CUtensorMap* m, int c0, int c1, uint32_t bar, uint64_t pol) {
  asm volatile("cp.async.bulk.tensor.2d.shared::cluster.global.mbarrier::complete_tx::bytes.multicast::cluster.L2::cache_hint [%0], [%1, {%3, %4}], [%2], %5, %6;"
               ::"r"(dst), "l"(m), "r"(bar), "r"(c0), "r"(c1), "h"((uint16_t)3), "l"(pol) : "memory");
}
__device__ __forceinline__ void tma_store(const CUtensorMap* m, int c0, int c1, uint32_t src) {
  asm volatile("cp.async.bulk.tensor.2d.global.shared::cta.bulk_group [%0, {%2, %3}], [%1];" ::"l"(m), "r"(src), "r"(c0), "r"(c1) : "memory");
}
__device__ __forceinline__ void fence_async_smem() { asm volatile("fence.proxy.async.shared::cta;" ::: "memory"); }
__device__ __forceinline__ void bar_sync(int id, int n) { asm volatile("bar.sync %0, %1;" ::"r"(id), "r"(n) : "memory"); }
__device__ __forceinline__ void bar_arrive(int id, int n) { asm volatile("bar.arrive %0, %1;" ::"r"(id), "r"(n) : "memory"); }
__device__ __forceinline__ bool bar_any(int id, int n, bool v) {
  uint32_t r;
  asm volatile("{\n.reg .pred p, q;\nsetp.ne.u32 q, %3, 0;\nbar.red.or.pred p, %1, %2, q;\nselp.u32 %0, 1, 0, p;\n}\n"
               : "=r"(r) : "r"(id), "r"(n), "r"((uint32_t)v) : "memory");
  return r;
}
__device__ __forceinline__ void cluster_arrive() { asm volatile("barrier.cluster.arrive.relaxed.aligned;" ::: "memory"); }
__device__ __forceinline__ void cluster_wait() { asm volatile("barrier.cluster.wait.aligned;" ::: "memory"); }
__device__ __forceinline__ bool elect_one() {
  uint32_t r;
  asm volatile("{\n.reg .pred p;\nelect.sync _|p, 0xffffffff;\nselp.u32 %0, 1, 0, p;\n}\n" : "=r"(r));
  return r;
}
__device__ __forceinline__ float ex2(float x) {
  float y;
  asm("ex2.approx.ftz.f32 %0, %1;" : "=f"(y) : "f"(x));
  return y;
}
__device__ __forceinline__ float rcp(float x) {
  float y;
  asm("rcp.approx.ftz.f32 %0, %1;" : "=f"(y) : "f"(x));
  return y;
}
__device__ __forceinline__ uint32_t pack(float lo, float hi) {
  uint32_t p;
  asm("cvt.rn.bf16x2.f32 %0, %1, %2;" : "=r"(p) : "f"(hi), "f"(lo));
  return p;
}
__device__ __forceinline__ void stsm4(uint32_t addr, uint32_t r0, uint32_t r1, uint32_t r2, uint32_t r3) {
  asm volatile("stmatrix.sync.aligned.m8n8.x4.shared.b16 [%0], {%1, %2, %3, %4};" ::"r"(addr), "r"(r0), "r"(r1), "r"(r2), "r"(r3) : "memory");
}
__device__ __forceinline__ void stsm4t(uint32_t addr, uint32_t r0, uint32_t r1, uint32_t r2, uint32_t r3) {
  asm volatile("stmatrix.sync.aligned.m8n8.x4.trans.shared.b16 [%0], {%1, %2, %3, %4};" ::"r"(addr), "r"(r0), "r"(r1), "r"(r2), "r"(r3) : "memory");
}
__device__ __forceinline__ void stsm2t(uint32_t addr, uint32_t r0, uint32_t r1) {
  asm volatile("stmatrix.sync.aligned.m8n8.x2.trans.shared.b16 [%0], {%1, %2};" ::"r"(addr), "r"(r0), "r"(r1) : "memory");
}
__device__ __forceinline__ void st16(void* p, uint32_t a, uint32_t b, uint32_t c, uint32_t d) {
  asm volatile("st.global.v4.b32 [%0], {%1, %2, %3, %4};" ::"l"(p), "r"(a), "r"(b), "r"(c), "r"(d) : "memory");
}
__device__ __forceinline__ uint32_t opaque_tid() {
  uint32_t t;
  asm volatile("mov.u32 %0, %%tid.x;" : "=r"(t));
  return t;
}
__device__ __forceinline__ void order_point(float a, float b, uint32_t addr, uint32_t never) {
  asm volatile("{\n.reg .pred p;\nsetp.ne.u32 p, %3, 0;\n@p st.shared.v2.f32 [%0], {%1, %2};\n}\n" ::"r"(addr), "f"(a), "f"(b), "r"(never) : "memory");
}
__device__ __forceinline__ float quad_sum(float v) {
  v += __shfl_xor_sync(0xffffffffu, v, 1);
  v += __shfl_xor_sync(0xffffffffu, v, 2);
  return v;
}
__device__ __forceinline__ bool unsafe(float l) { return !(l >= 8.673617379884035e-19f && l <= 1.152921504606847e18f); }
__device__ __forceinline__ __nv_bfloat16* o_tile(int round, int row) {
  return g_o + ((size_t)((blockIdx.x >> 3) * 64 + (round * 8 + (blockIdx.x & 7)) * 2) * 224 + row) * 64;
}

struct Cursor {
  uint32_t s, par;
  template <int N> __device__ __forceinline__ void next() {
    if (N == 5 && s == 3) { s = 6; return; }
    if (++s == 7) { s = 0; par ^= 1; }
  }
};

__device__ __forceinline__ void slow_rows(uint32_t qreg  , int w, const __nv_bfloat16* __restrict__ K,
                                          const __nv_bfloat16* __restrict__ V, __nv_bfloat16* out) {
  const int t = threadIdx.x & 127;
  const bool active = (w == 0) || (t < 96);
  const int tile = t >> 6, r = t & 63;
  uint32_t q2[64];
#pragma unroll
  for (int d = 0; d < 128; d++) {
    uint32_t addr;
    if (w == 1 && tile == 1) {
      const int kap = 16 * (d >> 5) + 2 * ((d & 31) >> 2) + (d & 1), h = ((d >> 1) ^ (d >> 3)) & 1;
      const int chunk = 2 * ((r >> 3) & 3) + h;
      addr = qreg + 16384 + kap * 128 + ((chunk ^ (kap & 7)) << 4) + (r & 7) * 2;
    } else {
      addr = qreg + tile * 16384 + d * 128 + (((r >> 3) ^ (d & 7)) << 4) + (r & 7) * 2;
    }
    uint16_t v;
    asm volatile("ld.shared.u16 %0, [%1];" : "=h"(v) : "r"(addr));
    if (d & 1) q2[d >> 1] |= (uint32_t)v << 16; else q2[d >> 1] = v;
  }
  if (w == 0) bar_sync(NB_SLOW, 128); else bar_sync(NB_SLOW + 1, 128);
  auto score = [&](int j) {
    const uint4* kr = reinterpret_cast<const uint4*>(K + (size_t)j * 128);
    float s = 0.f;
#pragma unroll
    for (int c = 0; c < 16; c++) {
      const uint4 kv = __ldg(kr + c);
      const uint32_t kk[4] = {kv.x, kv.y, kv.z, kv.w};
#pragma unroll
      for (int e = 0; e < 4; e++) {
        s = fmaf(__uint_as_float(q2[c * 4 + e] << 16), __uint_as_float(kk[e] << 16), s);
        s = fmaf(__uint_as_float(q2[c * 4 + e] & 0xffff0000u), __uint_as_float(kk[e] & 0xffff0000u), s);
      }
    }
    return s;
  };
  if (active) {
    float m = -INFINITY;
    for (int j = 0; j < 1024; j++) {
      const float s = score(j);
      m = (s > m || s != s) ? s : m;
    }
    for (int half = 0; half < 2; half++) {
      float o[64];
#pragma unroll
      for (int i = 0; i < 64; i++) o[i] = 0.f;
      float l = 0.f;
      for (int j = 0; j < 1024; j++) {
        const float pf = exp2f(score(j) - m);
        l += pf;
        const float pr = __bfloat162float(__float2bfloat16(pf));
        const uint4* vr = reinterpret_cast<const uint4*>(V + (size_t)j * 128 + half * 64);
#pragma unroll
        for (int c = 0; c < 8; c++) {
          const uint4 vv = __ldg(vr + c);
          const uint32_t kk[4] = {vv.x, vv.y, vv.z, vv.w};
#pragma unroll
          for (int e = 0; e < 4; e++) {
            o[c * 8 + 2 * e] = fmaf(pr, __uint_as_float(kk[e] << 16), o[c * 8 + 2 * e]);
            o[c * 8 + 2 * e + 1] = fmaf(pr, __uint_as_float(kk[e] & 0xffff0000u), o[c * 8 + 2 * e + 1]);
          }
        }
      }
      const float inv = 1.f / l;
#pragma unroll
      for (int c = 0; c < 8; c++) {
        const float* x = &o[(c >> 2) * 32 + (c & 3) * 2];
        st16(out + half * (224 * 64) + t * 64 + c * 8, pack(x[0] * inv, x[1] * inv), pack(x[8] * inv, x[9] * inv),
             pack(x[16] * inv, x[17] * inv), pack(x[24] * inv, x[25] * inv));
      }
    }
  }
}

template <int A0, int A1>
__device__ __forceinline__ void pack_o(const float (&o)[64], float i0, float i1, uint32_t (&r)[32]) {
#pragma unroll
  for (int a = A0; a < A1; a++) {
#pragma unroll
    for (int i = 0; i < 4; i++) {
      const float* x = &o[16 * a + 4 * i];
      r[8 * a + i] = pack(x[0] * i0, x[1] * i0);
      r[8 * a + 4 + i] = pack(x[2] * i1, x[3] * i1);
    }
  }
}
struct OutRegs {
  uint32_t a[32], b[32];
  char *pa, *pb;
  float i0, i1;
  uint32_t never;
  bool on, on2, sync;
};
template <int N>
__device__ __forceinline__ void store_piece(const OutRegs& o) {
  const uint32_t* r = N < 8 ? &o.a[4 * N] : &o.b[4 * (N - 8)];
  constexpr int blk = (N & 7) >> 1;
  constexpr int off = (blk >> 1) * (224 * 128) + (blk & 1) * 64 + (N & 1) * 1024;
  if ((N >= 8 && (N & 1)) ? o.on2 : o.on) st16((N < 8 ? o.pa : o.pb) + off, r[0], r[1], r[2], r[3]);
}

template <int NA>
__device__ __forceinline__ void proj_head(float (&acc)[NA], uint32_t W, uint32_t sbase) {
  const uint32_t full0 = sbase + BAR_OFF + BAR_FULL;
  const uint32_t dbase = (sbase & 0x3FFFF) >> 4;
  const uint32_t aW = dbase + SLOT_D + W * 1024, aX = dbase;
  mbar_wait(full0, 0);
  mbar_wait(full0 + 8, 0);
  wg_fence();
  mma_proj0(acc, desc(aW), desc(aX), 0);
#pragma unroll
  for (int ks = 1; ks < 4; ks++) mma_proj(acc, desc(aW + ks * 128), desc(aX + ks * 2), 1);
  wg_commit();
  mbar_wait(full0 + 16, 0);
  wg_fence();
#pragma unroll
  for (int ks = 0; ks < 4; ks++) mma_proj(acc, desc(aW + (4 + ks) * 128), desc(aX + 2 * SLOT_D + ks * 2), 1);
  wg_commit();
}
struct ProjState { Cursor c; uint32_t prevX, prevW; };
template <int ST, int NA>
__device__ __forceinline__ void proj_block(float (&acc)[NA], uint32_t W, ProjState& st, uint32_t rpar  ,
                                           uint32_t sbase, uint32_t rel, bool rel_pred, OutRegs& o, const float (&oB)[64],
                                           bool signal = false, bool released = false) {
  const uint32_t full0 = sbase + BAR_OFF + BAR_FULL;
  const uint32_t dbase = (sbase & 0x3FFFF) >> 4;
  uint32_t sW, pW;
#pragma unroll
  for (int half = 0; half < 2; half++) {
    const uint32_t sX = st.c.s, pX = st.c.par ^ ((sX & 6) == 4 ? rpar : 0);
    st.c.template next<7>();
    if (half == 0) {
      sW = st.c.s;
      pW = st.c.par ^ ((sW & 6) == 4 ? rpar : 0);
      st.c.template next<7>();
    }
    const uint32_t aW = dbase + sW * SLOT_D + W * 1024;
    if (ST == 0 && half == 0 && W == 0 && o.sync) bar_sync(NB_LEAD, 256);
    if (half == 0) mbar_wait(full0 + sW * 8, pW);
    mbar_wait(full0 + sX * 8, pX);
    const uint32_t aX = dbase + sX * SLOT_D;
    wg_fence();
#pragma unroll
    for (int ks = 0; ks < 4; ks++) mma_proj(acc, desc(aW + (half * 4 + ks) * 128), desc(aX + ks * 2), 1);
    wg_commit();
    if (ST < 0 && half == 1 && signal) bar_arrive(NB_LEAD, 256);
    if (ST >= 0) {
      constexpr int n0 = 8 * (ST & 1);
      if (half == 0) { store_piece<n0>(o); store_piece<n0 + 1>(o); store_piece<n0 + 2>(o); store_piece<n0 + 3>(o); }
      else { store_piece<n0 + 4>(o); store_piece<n0 + 5>(o); store_piece<n0 + 6>(o); store_piece<n0 + 7>(o); }
      if (ST == 0) {
        mbar_wait(full0 + sX * 8, pX);
        if (half == 0) pack_o<0, 2>(oB, o.i0, o.i1, o.b); else pack_o<2, 4>(oB, o.i0, o.i1, o.b);
        order_point(__uint_as_float(o.b[16 * half + 7]), __uint_as_float(o.b[16 * half + 15]), sbase, o.never);
      }
    }
    wg_wait<1>();
    release(rel + st.prevX * 8, rel_pred && !(half == 0 && released));
    if (half == 0) release(rel + st.prevW * 8, rel_pred && !released);
    if (half == 1) st.prevW = sW;
    st.prevX = sX;
  }
}
template <int NA>
__device__ __forceinline__ void proj_rest(float (&acc)[NA], uint32_t W, int round, uint32_t sbase, uint32_t rel, bool rel_pred, OutRegs& o,
                                          const float (&oB)[64]) {
  ProjState st{Cursor{3, 0}, 2, 1};
  const uint32_t rpar = round & 1;
  wg_wait<1>();
  if (rel_pred) mbar_arrive_cluster(rel);
  proj_block<0>(acc, W, st, rpar, sbase, rel, rel_pred, o, oB);
  proj_block<1>(acc, W, st, rpar, sbase, rel, rel_pred, o, oB);
  if (round > 0) mbar_arrive(sbase + BAR_OFF + BAR_OST + W * 8);
  const int nkb = round == 4 ? 32 : 8;
#pragma unroll 1
  for (int kb = 3; kb < nkb; kb++) {
    bool released = false;
    if (kb == nkb - 1 && W == 1) {
      wg_wait<0>();
      if (rel_pred) { mbar_arrive_cluster(rel + st.prevX * 8); mbar_arrive_cluster(rel + st.prevW * 8); }
      released = true;
      bar_sync(NB_LEAD, 256);
    }
    proj_block<-1>(acc, W, st, rpar, sbase, rel, rel_pred, o, oB, kb == nkb - 1 && W == 0, released);
  }
  wg_wait<0>();
  pin(acc);
  if (rel_pred) { mbar_arrive_cluster(rel + st.prevX * 8); mbar_arrive_cluster(rel + st.prevW * 8); }
}

template <bool SP, int NT>
__device__ __forceinline__ void issue_qk(float (&s)[NT / 2], uint32_t aQ_, uint32_t aK, uint32_t meta, const uint32_t* qf = nullptr) {
  uint32_t aQ;
  asm volatile("mov.b32 %0, %1;" : "=r"(aQ) : "r"(aQ_));
  if (SP) {
    mma_qk_sp0(s, desc(aQ), desc2(aK), 0, meta);
#pragma unroll
    for (int ks = 1; ks < 3; ks++) mma_qk_sp(s, desc(aQ + ks * 128), desc2(aK + (ks >> 1) * 64 + (ks & 1) * 4), 1, meta);
    mma_qk_spr(s, qf[0], qf[1], qf[2], qf[3], desc2(aK + 68), 1, meta);
  } else {
    mma_qk0(s, desc(aQ), desc2(aK), 0);
#pragma unroll
    for (int ks = 1; ks < 8; ks++) mma_qk(s, desc(aQ + ks * 128), desc2(aK + (ks >> 2) * 64 + (ks & 3) * 2), 1);
  }
}
template <bool SP, int NT>
__device__ __forceinline__ void issue_pv(float (&o)[64], const uint32_t (&p)[24], uint32_t aV, uint32_t meta) {
  const uint32_t lo = aV | (64u << 16);
  constexpr int K0 = NT == 64;
  if (K0) {
    if (SP) mma_pv_sp0(o, p[0], p[1], p[2], p[3], desc2(lo), 0, meta);
    else mma_pv0(o, p[0], p[1], p[2], p[3], desc2(lo), 0);
  }
  if (SP) {
#pragma unroll
    for (int ks = K0; ks < NT / 32; ks++) mma_pv_sp(o, p[4 * ks], p[4 * ks + 1], p[4 * ks + 2], p[4 * ks + 3], desc2(lo + ks * 512), 1, meta);
  } else {
#pragma unroll
    for (int ks = K0; ks < NT / 16; ks++) mma_pv(o, p[4 * ks], p[4 * ks + 1], p[4 * ks + 2], p[4 * ks + 3], desc2(lo + ks * 256), 1);
  }
}
template <bool SP, int NT>
__device__ __forceinline__ void exp_inplace(float (&s)[NT / 2], float& l0, float& l1) {
#pragma unroll
  for (int i = 0; i < NT / 8; i++) {
    if (SP) {
      s[4 * i] = ex2(s[4 * i] + s[4 * i + 2]);
      s[4 * i + 1] = ex2(s[4 * i + 1] + s[4 * i + 3]);
      if (i & 1) l1 += s[4 * i] + s[4 * i + 1]; else l0 += s[4 * i] + s[4 * i + 1];
    } else {
      s[4 * i] = ex2(s[4 * i]);
      s[4 * i + 1] = ex2(s[4 * i + 1]);
      s[4 * i + 2] = ex2(s[4 * i + 2]);
      s[4 * i + 3] = ex2(s[4 * i + 3]);
      l0 += s[4 * i] + s[4 * i + 1];
      l1 += s[4 * i + 2] + s[4 * i + 3];
    }
  }
}
template <bool SP, int NT>
__device__ __forceinline__ void convert_p(const float (&s)[NT / 2], uint32_t (&p)[24]) {
  if (SP) {
    const uint32_t lane = opaque_tid() & 31;
    const bool odd = lane & 1;
    const int srcA = (lane & 28) | ((lane & 1) << 1) | ((lane >> 1) & 1);
#pragma unroll
    for (int h = 0; h < NT / 16; h++) {
      const uint32_t p0 = pack(s[8 * h], s[8 * h + 1]), p1 = pack(s[8 * h + 4], s[8 * h + 5]);
      p[2 * h] = __shfl_sync(0xffffffffu, odd ? p1 : p0, srcA);
      p[2 * h + 1] = __shfl_sync(0xffffffffu, odd ? p0 : p1, srcA ^ 1);
    }
  } else {
#pragma unroll
    for (int i = 0; i < NT / 4; i++) p[i] = pack(s[2 * i], s[2 * i + 1]);
  }
}

template <int W>
__device__ __forceinline__ void attention(int round, uint32_t sbase, uint32_t rel, bool rel_pred, uint32_t never, uint32_t meta,
                                          float (&s0)[32], float (&oB)[64], OutRegs& og) {
  constexpr bool SPB = W == 1;
  const uint32_t full0 = sbase + BAR_OFF + BAR_FULL;
  const uint32_t dbase = (sbase & 0x3FFFF) >> 4;
  const uint32_t aQA = dbase + (4 + W) * SLOT_D, aQB = aQA + 1024;
  float oA[64];
  uint32_t pr[24];
  float lA0 = 0.f, lA1 = 0.f, lB0 = 0.f, lB1 = 0.f;
  Cursor c{3, 1};
  uint32_t sK = 3, sV = 3;
  uint32_t qf[4];
  if (SPB) {
    const uint32_t t = opaque_tid();
    const uint32_t mi = (t >> 3) & 3, r7 = t & 7, wp = (t >> 5) & 3;
    asm volatile("ldmatrix.sync.aligned.m8n8.x4.trans.shared.b16 {%0, %1, %2, %3}, [%4];"
                 : "=r"(qf[0]), "=r"(qf[1]), "=r"(qf[2]), "=r"(qf[3])
                 : "r"(sbase + 5 * SLOT_BYTES + 16384 + (48 + 8 * (mi >> 1) + r7) * 128 + (((2 * wp + (mi & 1)) ^ r7) << 4)) : "memory");
  }
  wg_wait<0>();
  pin(s0);
  exp_inplace<false, 64>(s0, lA0, lA1);
  convert_p<false, 64>(s0, pr);
  mbar_wait(full0 + sV * 8, c.par);
#define GROUP1(NT, NEXT)                                          \
  {                                                               \
    float s[NT / 2];                                              \
    wg_fence();                                                   \
    bar_sync(NB_ORD + W, 256);                                    \
    if (SPB) {                                                    \
      issue_pv<false, NT>(oA, pr, dbase + sV * SLOT_D + (NT == 64 ? 1024 : 0), meta); \
      issue_qk<true, NT>(s, aQB, dbase + sK * SLOT_D, meta, qf);  \
      wg_commit();                                                \
      bar_arrive(NB_ORD + (1 - W), 256);                          \
      wg_wait<0>();                                               \
      pin(s);                                                     \
      if (rel_pred) mbar_arrive_cluster(rel + (NT == 64 ? 0 : sK * 8)); \
      exp_inplace<true, NT>(s, lB0, lB1);                         \
      convert_p<true, NT>(s, pr);                                 \
      if (NEXT) c.next<5>();                                      \
      sK = c.s;                                                   \
      mbar_wait(full0 + sK * 8, c.par);                           \
    } else {                                                      \
      issue_qk<false, NT>(s, aQB, dbase + sK * SLOT_D, meta);     \
      wg_commit();                                                \
      issue_pv<false, NT>(oA, pr, dbase + sV * SLOT_D + (NT == 64 ? 1024 : 0), meta); \
      wg_commit();                                                \
      bar_arrive(NB_ORD + (1 - W), 256);                          \
      wg_wait<1>();                                               \
      pin(s);                                                     \
      if (rel_pred) mbar_arrive_cluster(rel + (NT == 64 ? 0 : sK * 8)); \
        \
      mbar_wait(full0 + sV * 8, c.par);                           \
      mbar_wait(full0 + sV * 8, c.par);                           \
      pin(s);                                                     \
      exp_inplace<false, NT>(s, lB0, lB1);                        \
      order_point(lB0, lB1, sbase, never);                        \
      wg_wait<0>();                                               \
      if (NEXT) c.next<5>();                                      \
      sK = c.s;                                                   \
      mbar_wait(full0 + sK * 8, c.par);                           \
      pin(s);                                                     \
      convert_p<false, NT>(s, pr);                                \
    }                                                             \
  }
#define GROUP2(NT)                                                \
  {                                                               \
    float s[48];                                                  \
    wg_fence();                                                   \
    bar_sync(NB_ORD + W, 256);                                    \
    issue_qk<false, 96>(s, aQA, dbase + sK * SLOT_D, meta);       \
    if (!SPB) wg_commit();                                        \
    issue_pv<SPB, NT>(oB, pr, dbase + sV * SLOT_D + (NT == 64 ? 1024 : 0), meta); \
    wg_commit();                                                  \
    bar_arrive(NB_ORD + (1 - W), 256);                            \
    if (SPB) {   \
      wg_wait<0>();                                               \
      pin(s);                                                     \
      if (rel_pred) mbar_arrive_cluster(rel + sV * 8);            \
      exp_inplace<false, 96>(s, lA0, lA1);                        \
      convert_p<false, 96>(s, pr);                                \
      c.next<5>();                                                \
      if (NT == 64) c.next<5>();                                  \
      sV = c.s;                                                   \
      mbar_wait(full0 + sV * 8, c.par);                             \
    } else {                                                      \
      wg_wait<1>();                                               \
      pin(s);                                                     \
      exp_inplace<false, 96>(s, lA0, lA1);                        \
      order_point(lA0, lA1, sbase, never);                        \
      wg_wait<0>();                                               \
      if (rel_pred) mbar_arrive_cluster(rel + sV * 8);            \
      c.next<5>();                                                \
      if (NT == 64) c.next<5>();                                  \
      sV = c.s;                                                   \
      mbar_wait(full0 + sV * 8, c.par);                             \
      pin(s);                                                     \
      convert_p<false, 96>(s, pr);                                \
    }                                                             \
  }
  GROUP1(64, true)
  mbar_wait(full0 + sK * 8, c.par);
  GROUP2(64)
#pragma unroll 1
  for (int j = 0;; j++) {
    GROUP1(96, (j < 9))
    if (j == 9) break;
    GROUP2(96)
  }
#undef GROUP1
#undef GROUP2
  bar_sync(NB_ORD + W, 256);
  wg_fence();
  issue_pv<SPB, 96>(oB, pr, dbase + sV * SLOT_D, meta);
  wg_commit();
  if (W == 0) bar_arrive(NB_ORD + 1, 256);
  lA0 = quad_sum(lA0);
  lA1 = quad_sum(lA1);
  if (SPB) { lB0 = quad_sum(lB0 + lB1); lB1 = lB0; } else { lB0 = quad_sum(lB0); lB1 = quad_sum(lB1); }
  bool bad = unsafe(lA0) || unsafe(lA1) || unsafe(lB0) || unsafe(lB1);
  bad = __any_sync(0xffffffffu, bar_any(NB_VOTE + W, 128, bad));
  og.i0 = rcp(lB0);
  og.i1 = rcp(lB1);
  pin(oA);
  if (!bad) { release(rel + (4 + W) * 8, rel_pred); release(rel + (4 + W) * 8, rel_pred); }
  pack_o<0, 4>(oA, rcp(lA0), rcp(lA1), og.a);
  {
    const uint32_t t = opaque_tid();
    const uint32_t wp = (t >> 5) & 3, g = (t >> 2) & 7, cq = t & 3;
    char* base = reinterpret_cast<char*>(o_tile(round, W * 128)) + g * 128 + cq * 16;
    og.pa = base + wp * 2048;
    og.pb = base + 8192 + wp * (SPB ? 1024 : 2048);
    og.on = !bad;
    og.on2 = !bad && !SPB;
    og.sync = true;
  }
  wg_wait<0>();
  pin(oB);
  release(rel + sV * 8, rel_pred);
  if (SPB) {
#pragma unroll
    for (int i = 0; i < 16; i++) {
      oB[4 * i] += oB[4 * i + 2];
      oB[4 * i + 1] += oB[4 * i + 3];
      oB[4 * i + 2] = oB[4 * i + 3] = 0.f;
    }
  }
}

template <int NA>
__device__ __forceinline__ void out_epilogue(const float (&acc)[NA], uint32_t W, uint32_t sbase) {
  cluster_arrive();
  mbar_wait(sbase + BAR_OFF + BAR_EMPTY + (5 + W) * 8, 0);
  const uint32_t t = opaque_tid();
  const uint32_t lane = t & 31, wp = (t >> 5) & 3, mi = lane >> 3, r7 = lane & 7;
  const uint32_t base = sbase + (5 + W) * SLOT_BYTES + (8 * (mi >> 1) + r7) * 128 + (((2 * wp + (mi & 1)) ^ r7) << 4);
#pragma unroll
  for (int i = 0; i < NA / 4; i += 2) {
    if (i + 1 < NA / 4)
      stsm4t(base + i * 1024, pack(acc[4 * i], acc[4 * i + 1]), pack(acc[4 * i + 2], acc[4 * i + 3]),
             pack(acc[(4 * i + 4) % NA], acc[(4 * i + 5) % NA]), pack(acc[(4 * i + 6) % NA], acc[(4 * i + 7) % NA]));
    else
      stsm2t(base + i * 1024, pack(acc[4 * i], acc[4 * i + 1]), pack(acc[4 * i + 2], acc[4 * i + 3]));
    if (i == 12 || i + 2 >= NA / 4) {
      fence_async_smem();
      mbar_arrive(sbase + BAR_OFF + (i == 12 ? BAR_OST : BAR_OST2) + W * 8);
    }
  }
}

__device__ __forceinline__ void consumer(const Params& p, uint32_t W, uint32_t sbase, uint32_t rank) {
  const uint32_t empty0 = sbase + BAR_OFF + BAR_EMPTY;
  const uint32_t tid = threadIdx.x;
  const bool rel_pred = (tid & 95) == 0;
  const uint32_t rel = mapa(empty0, ((tid >> 5) & 1) ? (rank ^ 1) : rank);
  const uint32_t qreg = sbase + 4 * SLOT_BYTES;
  const uint32_t never = p.zero;
  uint32_t meta;
  asm volatile("mov.b32 %0, %1;" : "=r"(meta) : "r"((tid & 2) ? (0x44444444u | (tid << 24 & 0x88000000u)) : 0x44EEEE44u));
  const bool shortened = p.helpers && blockIdx.x >= 64;
  float acc[112], oB[64];
  OutRegs og;
  og.on = og.on2 = og.sync = false;
  og.pa = og.pb = nullptr;
  og.i0 = og.i1 = 0.f;
  og.never = never;
#pragma unroll
  for (int i = 0; i < 64; i++) oB[i] = 0.f;
#pragma unroll
  for (int i = 0; i < 32; i++) og.a[i] = 0;

#pragma unroll 1
  for (int round = 0;; round++) {
    if (round == 4 && shortened) break;
    proj_head(acc, W, sbase);
    if (W == 1 && og.sync) bar_arrive(NB_LEAD, 256);
    proj_rest(acc, W, round, sbase, rel, rel_pred, og, oB);
    if (round == 4) {
      out_epilogue(acc, W, sbase);
      return;
    }
    {
      mbar_wait(empty0 + 4 * 8, 0);
      mbar_wait(empty0 + 5 * 8, 0);
      const float sc = 0.12751743f;
      const uint32_t t = opaque_tid();
      const uint32_t lane = t & 31, wp = (t >> 5) & 3, mi = lane >> 3, r7 = lane & 7;
      const uint32_t dd = 64 * W + 16 * wp + 8 * (mi & 1) + r7;
      const uint32_t rowa = qreg + dd * 128;
#pragma unroll
      for (int i = 0; i < 28; i += 2) {
        uint32_t addr;
        if (i >= 24) {
          const uint32_t kap = 16 * (dd >> 5) + 2 * ((dd & 31) >> 2) + (dd & 1), h = ((dd >> 1) ^ (dd >> 3)) & 1;
          const uint32_t chunk = 2 * (i - 24 + (mi >> 1)) + h;
          addr = qreg + 3 * 16384 + kap * 128 + ((chunk ^ (kap & 7)) << 4);
        } else {
          addr = rowa + (i >> 3) * 16384 + ((((i & 7) + (mi >> 1)) ^ r7) << 4);
        }
        stsm4(addr, pack(acc[4 * i] * sc, acc[4 * i + 1] * sc), pack(acc[4 * i + 2] * sc, acc[4 * i + 3] * sc),
              pack(acc[4 * i + 4] * sc, acc[4 * i + 5] * sc), pack(acc[4 * i + 6] * sc, acc[4 * i + 7] * sc));
        if (i == 6 && W == 1) {
          fence_async_smem();
          bar_sync(NB_QREADY, 256);
        }
      }
      fence_async_smem();
      mbar_wait(sbase + BAR_OFF + BAR_FULL + 3 * 8, 1);
      if (W == 0) bar_sync(NB_QREADY, 256); else bar_sync(NB_Q1, 128);
    }
    float s0[32];
    {
      const uint32_t dbase = (sbase & 0x3FFFF) >> 4;
      wg_fence();
      issue_qk<false, 64>(s0, dbase + (4 + W) * SLOT_D, dbase + 3 * SLOT_D, meta);
      wg_commit();
      if (W == 1) bar_arrive(NB_ORD, 256);
    }
    if (W == 0) attention<0>(round, sbase, rel, rel_pred, never, meta, s0, oB, og);
    else attention<1>(round, sbase, rel, rel_pred, never, meta, s0, oB, og);
    if (!og.on) {
      const int pair = blockIdx.x >> 3, head = round * 8 + (blockIdx.x & 7);
      const size_t off = (size_t)((pair & 7) * 32 + head) * (1024 * 128);
      slow_rows(qreg + W * SLOT_BYTES, W, p.kp[pair >> 3] + off, p.vp[pair >> 3] + off, o_tile(round, W * 128));
      if (rel_pred) { mbar_arrive_cluster(rel + (4 + W) * 8); mbar_arrive_cluster(rel + (4 + W) * 8); }
#pragma unroll
      for (int i = 0; i < 64; i++) oB[i] = 0.f;
#pragma unroll
      for (int i = 0; i < 32; i++) og.a[i] = 0;
    }
  }
  {
    float acc2[100];
    proj_head(acc2, W, sbase);
    if (W == 1) bar_arrive(NB_LEAD, 256);
    proj_rest(acc2, W, 4, sbase, rel, rel_pred, og, oB);
    out_epilogue(acc2, W, sbase);
  }
}

__device__ __forceinline__ void helper_consumer(uint32_t W, uint32_t sbase) {
  const uint32_t full0 = sbase + BAR_OFF + BAR_FULL, empty0 = sbase + BAR_OFF + BAR_EMPTY;
  const uint32_t dbase = (sbase & 0x3FFFF) >> 4;
  const bool rel_pred = (threadIdx.x & 95) == 0;
  float a0[96], a1[96];
#pragma unroll
  for (int i = 0; i < 96; i++) a0[i] = a1[i] = 0.f;
  uint32_t st = 0, par = 0, prev = 0;
#pragma unroll 1
  for (int k = 0; k < 64; k++) {
    mbar_wait(full0 + st * 8, par);
    const uint32_t aW = dbase + 2 * st * SLOT_D + W * 1024, aX = dbase + (2 * st + 1) * SLOT_D;
    wg_fence();
#pragma unroll
    for (int ks = 0; ks < 4; ks++) {
      mma_proj(a0, desc(aW + ks * 128), desc(aX + ks * 2), 1);
      mma_proj(a1, desc(aW + 512 + ks * 128), desc(aX + ks * 2), 1);
    }
    wg_commit();
    wg_wait<1>();
    if (k > 0 && rel_pred) mbar_arrive(empty0 + prev * 8);
    prev = st;
    if (++st == 3) { st = 0; par ^= 1; }
  }
  wg_wait<0>();
  pin(a0);
  pin(a1);
  cluster_arrive();
  bar_sync(NB_QREADY, 256);
  const uint32_t t = opaque_tid();
  const uint32_t lane = t & 31, wp = (t >> 5) & 3, mi = lane >> 3, r7 = lane & 7;
  const uint32_t base = sbase + 2 * W * SLOT_BYTES + (8 * (mi >> 1) + r7) * 128 + (((2 * wp + (mi & 1)) ^ r7) << 4);
#pragma unroll
  for (int i = 0; i < 24; i += 2) {
    stsm4t(base + i * 1024, pack(a0[4 * i], a0[4 * i + 1]), pack(a0[4 * i + 2], a0[4 * i + 3]), pack(a0[4 * i + 4], a0[4 * i + 5]),
           pack(a0[4 * i + 6], a0[4 * i + 7]));
    stsm4t(base + SLOT_BYTES + i * 1024, pack(a1[4 * i], a1[4 * i + 1]), pack(a1[4 * i + 2], a1[4 * i + 3]),
           pack(a1[4 * i + 4], a1[4 * i + 5]), pack(a1[4 * i + 6], a1[4 * i + 7]));
  }
  fence_async_smem();
  mbar_arrive(sbase + BAR_OFF + BAR_OST + W * 8);
}
__device__ __forceinline__ void helper_service(const Params& p, uint32_t sbase, int wid) {
  const uint32_t full0 = sbase + BAR_OFF + BAR_FULL, empty0 = sbase + BAR_OFF + BAR_EMPTY;
  const int h = blockIdx.x - 128;
  if (wid == 8) {
    uint32_t st = 0, par = 1;
#pragma unroll 1
    for (int k = 0; k < 64; k++) {
      if ((k & 15) == 0) {
        mbar_wait(sbase + BAR_OFF + BAR_FLAG + (k >> 4) * 8, 0);
        asm volatile("fence.proxy.async.global;" ::: "memory");
      }
      mbar_wait(empty0 + st * 8, par);
      if (elect_one()) {
        const uint32_t dst = sbase + 2 * st * SLOT_BYTES, bar = full0 + st * 8;
        mbar_expect_tx(bar, 32768 + 24576);
#pragma unroll
        for (int i = 0; i < 4; i++) tma_load5(dst + i * 8192, &p.wo64, h * 256 + i * 64, k * 2, bar);
#pragma unroll
        for (int b = 0; b < 8; b++) tma_load2(dst + SLOT_BYTES + b * 3072, &p.o24, 0, ((8 + b) * 64 + k) * 224 + 200, bar);
      }
      if (++st == 3) { st = 0; par ^= 1; }
    }
  } else if (wid == 10) {
#pragma unroll 1
    for (int i = 0; i < 4; i++) {
      if ((i & 1) == 0) mbar_wait(sbase + BAR_OFF + BAR_OST + (i >> 1) * 8, 0);
      if (elect_one()) {
#pragma unroll
        for (int b = 0; b < 8; b++) tma_store(&p.out24, 1024 + h * 256 + i * 64, b * 224 + 200, sbase + i * SLOT_BYTES + b * 3072);
      }
    }
    if (elect_one()) {
      asm volatile("cp.async.bulk.commit_group;" ::: "memory");
      asm volatile("cp.async.bulk.wait_group.read 0;" ::: "memory");
    }
  }
  __syncwarp();
}

__device__ __forceinline__ int okb(int kb) { return (((0x0132 >> ((kb >> 3) * 4)) & 3) << 3) | (kb & 7); }

template <int SEL>
__device__ __forceinline__ void loader(const Params& p, uint32_t sbase, uint32_t rank) {
  const uint32_t full0 = sbase + BAR_OFF + BAR_FULL, empty0 = sbase + BAR_OFF + BAR_EMPTY;
  const int pair = blockIdx.x >> 3, cc = blockIdx.x & 7, br = pair >> 3, b = pair & 7;
#pragma unroll 1
  for (int round = 0; round < 5; round++) {
    const bool oproj = round == 4;
    const int head = round * 8 + cc;
    const int kvrow = (b * 32 + head) * 1024;
    const char* pfp = reinterpret_cast<const char*>(SEL ? p.vp[br] : p.kp[br]) + (size_t)kvrow * 256 + (SEL ? 16 : 28) * 4096;
    const bool shortened = oproj && br == 1 && p.helpers;
    const CUtensorMap* m = SEL ? (oproj ? (shortened && rank ? &p.o88 : &p.o_ld) : &p.x[br]) : (oproj ? &p.wo[br] : &p.wq[br]);
    const int fixed = SEL ? (oproj ? pair * 64 : b) * 224 + rank * 112 : (oproj ? cc : head) * 128;
    const int nkb = oproj ? 32 : 8;
    Cursor c{round == 0 ? 6u : 0u, 1};
#pragma unroll 1
    for (int kb = round == 0 ? 2 : 0; kb < nkb; kb++) {
      if (SEL == 0) {
        c.next<7>();
        mbar_wait(empty0 + c.s * 8, c.par);
        if (elect_one()) {
          const uint32_t dst = sbase + c.s * SLOT_BYTES, bar = full0 + c.s * 8;
          mbar_expect_tx(bar, 32768);
          if (oproj) {
            tma_load5(dst, m, fixed, okb(kb) * 4, bar);
            tma_load5(dst + 16384, m, fixed + 64, okb(kb) * 4, bar);
          } else {
            tma_load2(dst, m, fixed, kb * 128, bar);
            tma_load2(dst + 16384, m, fixed + 64, kb * 128, bar);
          }
        }
        c.next<7>();
        c.next<7>();
      } else {
        if (oproj && (kb & 7) == 0) {
          mbar_wait(sbase + BAR_OFF + BAR_FLAG + (okb(kb) >> 3) * 8, 0);
          asm volatile("fence.proxy.async.global;" ::: "memory");
        }
#pragma unroll
        for (int half = 0; half < 2; half++) {
          mbar_wait(empty0 + c.s * 8, c.par);
          if (elect_one()) {
            mbar_expect_tx(full0 + c.s * 8, shortened ? 25600 : 28672);
            tma_load_mc(sbase + c.s * SLOT_BYTES + rank * 14336, m, oproj ? 0 : kb * 128 + half * 64,
                        oproj ? fixed + (okb(kb) * 2 + half) * 224 : fixed, full0 + c.s * 8, round >= 3 ? POL_FIRST : POL_NORMAL);
          }
          c.next<7>();
          if (half == 0) c.next<7>();
        }
      }
      if (!oproj && kb < 6) {
        const uint32_t bytes = (1 + (kb & 1)) * 4096;
        if (elect_one()) asm volatile("cp.async.bulk.prefetch.L2.global [%0], %1;" ::"l"(pfp), "r"(bytes) : "memory");
        pfp += bytes;
      }
    }
    if (oproj) break;
    const bool yield = br == 1;
    c = Cursor{SEL ? 1u : 3u, SEL ? 1u : 0u};
    uint32_t ps = 0, pp = 0;
#pragma unroll 1
    for (int j = SEL; j < 11; j++) {
      mbar_wait(empty0 + c.s * 8, c.par);
      if (yield && j > SEL) {
        mbar_wait_soft(full0 + ps * 8, pp);
        if (round == 0) __nanosleep(200);
      }
      ps = c.s;
      pp = c.par ^ 1;
      if (elect_one()) {
        const uint32_t dst = sbase + c.s * SLOT_BYTES, bar = full0 + c.s * 8;
        if (j > 0) {
          if (SEL == 1 && j == 3) mbar_arrive(bar);
          mbar_expect_tx(bar, 24576);
          tma_load4(dst, &p.kv[br][SEL][0], (kvrow + j * 96 - 32) >> 3, bar, POL_FIRST);
        } else {
          mbar_expect_tx(bar, 32768);
          tma_load4(dst, &p.kv[br][0][1], kvrow >> 3, bar, POL_FIRST);
          tma_load4(dst + 16384, &p.kv[br][1][1], kvrow >> 3, bar, POL_FIRST);
        }
      }
      c.next<5>();
      if (j > 0) c.next<5>();
      if (SEL == 0 && j == 1) c.next<5>();
    }
  }
}

__device__ __forceinline__ void storer(const Params& p, uint32_t sbase) {
  const uint32_t ost = sbase + BAR_OFF + BAR_OST;
  const int pair = blockIdx.x >> 3, cc = blockIdx.x & 7;
#pragma unroll 1
  for (int round = 0; round < 4; round++) {
    mbar_wait(ost, round & 1);
    mbar_wait(ost + 8, round & 1);
    if (elect_one()) {
      __threadfence();
      asm volatile("red.release.gpu.global.add.u32 [%0], 1;" ::"l"(&g_flags[pair * 4 + round]) : "memory");
    }
    __syncwarp();
  }
  cluster_arrive();
#pragma unroll
  for (int i = 0; i < 4; i++) {
    const int w = i >> 1, h = i & 1;
    mbar_wait((h ? sbase + BAR_OFF + BAR_OST2 : ost) + w * 8, 0);
    if (elect_one())
      tma_store(h && p.helpers && pair >= 8 ? &p.out88 : &p.out_st, (pair >> 3) * 1024 + cc * 128 + w * 64, (pair & 7) * 224 + h * 112, sbase + (5 + w) * SLOT_BYTES + h * 14336);
  }
  if (elect_one()) {
    asm volatile("cp.async.bulk.commit_group;" ::: "memory");
    asm volatile("cp.async.bulk.wait_group.read 0;" ::: "memory");
  }
  __syncwarp();
}

__device__ __forceinline__ void watcher(uint32_t sbase) {
  if (elect_one()) {
    const unsigned epoch = g_epoch[blockIdx.x];
    const unsigned target = (epoch + 1) * 8;
    const int first = blockIdx.x < 128 ? blockIdx.x >> 3 : 8, cnt = blockIdx.x < 128 ? 1 : 8;
#pragma unroll 1
    for (int i = 0; i < 4 * cnt; i++) {
      const int r = i / cnt;
      const unsigned* f = &g_flags[(first + i % cnt) * 4 + r];
      uint32_t n = 0;
      while (true) {
        unsigned v;
        asm volatile("ld.acquire.gpu.global.u32 %0, [%1];" : "=r"(v) : "l"(f) : "memory");
        if ((int)(v - target) >= 0) break;
        if (++n > SPIN_LIMIT) __trap();
        __nanosleep(500);
      }
      if (i % cnt == cnt - 1) mbar_arrive(sbase + BAR_OFF + BAR_FLAG + r * 8);
    }
    g_epoch[blockIdx.x] = epoch + 1;
  }
}

__global__ void __cluster_dims__(2, 1, 1) __launch_bounds__(384, 1) fused_kernel(const __grid_constant__ Params p) {
  extern __shared__ uint8_t smem_raw[];
  const uint32_t sbase = ((uint32_t)__cvta_generic_to_shared(smem_raw) + 1023) & ~1023u;
  uint32_t rank;
  asm("mov.u32 %0, %%cluster_ctarank;" : "=r"(rank));
  const int wid = __shfl_sync(0xffffffffu, threadIdx.x >> 5, 0);
  if (wid == 8 && elect_one()) {
#pragma unroll
    for (int i = 0; i < NSLOT; i++) mbar_init(sbase + BAR_OFF + BAR_FULL + i * 8, 1);
    asm volatile("fence.mbarrier_init.release.cluster;" ::: "memory");
    fence_async_smem();
  } else if (wid == 9 && elect_one()) {
#pragma unroll
    for (int i = 0; i < NSLOT; i++) mbar_init(sbase + BAR_OFF + BAR_EMPTY + i * 8, 4);
#pragma unroll
    for (int i = 0; i < 2; i++) {
      mbar_init(sbase + BAR_OFF + BAR_OST + i * 8, 128);
      mbar_init(sbase + BAR_OFF + BAR_OST2 + i * 8, 128);
    }
#pragma unroll
    for (int i = 0; i < 4; i++) mbar_init(sbase + BAR_OFF + BAR_FLAG + i * 8, 1);
    asm volatile("fence.mbarrier_init.release.cluster;" ::: "memory");
  }
  __syncwarp();
  cluster_arrive();
  const int br = blockIdx.x >> 6;
  const bool helper = br == 2;
  if (helper) {
  } else if (wid == 8 && elect_one()) {
    const int b = (blockIdx.x >> 3) & 7, cc = blockIdx.x & 7;
#pragma unroll
    for (int i = 0; i < 6; i++) {
      const uint32_t dst = sbase + i * SLOT_BYTES, bar = sbase + BAR_OFF + BAR_FULL + i * 8;
      if (i % 3 == 1) {
        mbar_expect_tx(bar, 32768);
        tma_load2(dst, &p.wq[br], cc * 128, (i / 3) * 128, bar);
        tma_load2(dst + 16384, &p.wq[br], cc * 128 + 64, (i / 3) * 128, bar);
      } else {
        mbar_expect_tx(bar, 28672);
        tma_load2(dst, &p.x[br], (i / 3) * 128 + (i % 3) * 32, b * 224, bar);
        tma_load2(dst + 14336, &p.x[br], (i / 3) * 128 + (i % 3) * 32, b * 224 + 112, bar);
      }
    }
  } else if (wid == 10 && elect_one()) {
#pragma unroll
    for (int i = 0; i < 4; i++) asm volatile("prefetch.tensormap [%0];" ::"l"(&p.kv[br][i & 1][i >> 1]) : "memory");
  }
  __syncwarp();
  cluster_wait();
  if (wid >= 8) {
    asm volatile("setmaxnreg.dec.sync.aligned.u32 24;");
    if (helper && wid != 11) {
      cluster_arrive();
      helper_service(p, sbase, wid);
    } else if (wid == 10) {
      storer(p, sbase);
    } else {
      if (wid == 8) loader<0>(p, sbase, rank);
      else if (wid == 9) loader<1>(p, sbase, rank);
      else watcher(sbase);
      __syncwarp();
      cluster_arrive();
    }
    cluster_wait();
  } else {
    asm volatile("setmaxnreg.inc.sync.aligned.u32 240;");
    if (helper) helper_consumer(wid >> 2, sbase);
    else consumer(p, wid >> 2, sbase, rank);
    cluster_wait();
  }
}

typedef CUresult (*EncodeFn)(CUtensorMap*, CUtensorMapDataType, cuuint32_t, void*, const cuuint64_t*, const cuuint64_t*,
                             const cuuint32_t*, const cuuint32_t*, CUtensorMapInterleave, CUtensorMapSwizzle,
                             CUtensorMapL2promotion, CUtensorMapFloatOOBfill);

void make_map(EncodeFn enc, CUtensorMap* m, const void* ptr, int rank, const cuuint64_t* dims, const cuuint64_t* strides, const cuuint32_t* box) {
  const cuuint32_t es[5] = {1, 1, 1, 1, 1};
  enc(m, CU_TENSOR_MAP_DATA_TYPE_BFLOAT16, rank, const_cast<void*>(ptr), dims, strides, box, es, CU_TENSOR_MAP_INTERLEAVE_NONE,
      CU_TENSOR_MAP_SWIZZLE_128B, CU_TENSOR_MAP_L2_PROMOTION_L2_128B, CU_TENSOR_MAP_FLOAT_OOB_FILL_NONE);
}
void make_map2(EncodeFn enc, CUtensorMap* m, const void* ptr, uint64_t cols, uint64_t rows, uint32_t box_rows) {
  const cuuint64_t dims[2] = {cols, rows}, strides[1] = {cols * 2};
  const cuuint32_t box[2] = {64, box_rows};
  make_map(enc, m, ptr, 2, dims, strides, box);
}

}

extern "C" void kernel_launch(void* const* d_in, const int* in_sizes, int n_in, void* d_out, int out_size) {
  static EncodeFn enc = nullptr;
  static void* o_ptr = nullptr;
  static int helpers = 0;
  if (!enc) {
    cudaDriverEntryPointQueryResult qr;
    cudaGetDriverEntryPoint("cuTensorMapEncodeTiled", (void**)&enc, cudaEnableDefault, &qr);
    cudaGetSymbolAddress(&o_ptr, g_o);
    cudaFuncSetAttribute(fused_kernel, cudaFuncAttributeMaxDynamicSharedMemorySize, SMEM_TOTAL);
    cudaLaunchConfig_t cfg = {};
    cfg.gridDim = 132;
    cfg.blockDim = 384;
    cfg.dynamicSmemBytes = SMEM_TOTAL;
    int nclusters = 0;
    if (cudaOccupancyMaxActiveClusters(&nclusters, fused_kernel, &cfg) != cudaSuccess) { nclusters = 0; (void)cudaGetLastError(); }
    helpers = nclusters >= 66;
  }
  Params p;
  for (int br = 0; br < 2; br++) {
    make_map2(enc, &p.x[br], d_in[br * 5 + 0], 1024, 1792, 112);
    for (int t = 0; t < 2; t++) {
      for (int z = 0; z < 2; z++) {
        const cuuint64_t dims[4] = {64, 8, 2, 32768}, strides[3] = {256, 128, 2048};
        const cuuint32_t box[4] = {64, 8, 2, z ? 8u : 12u};
        make_map(enc, &p.kv[br][t][z], d_in[br * 5 + 1 + t], 4, dims, strides, box);
      }
    }
    make_map2(enc, &p.wq[br], d_in[br * 5 + 3], 4096, 1024, 128);
    {
      const cuuint64_t dims[5] = {1024, 2, 4, 4, 128}, strides[4] = {2048, 8 * 2048, 2 * 2048, 32 * 2048};
      const cuuint32_t box[5] = {64, 2, 4, 4, 4};
      make_map(enc, &p.wo[br], d_in[br * 5 + 4], 5, dims, strides, box);
    }
    p.kp[br] = (const __nv_bfloat16*)d_in[br * 5 + 1];
    p.vp[br] = (const __nv_bfloat16*)d_in[br * 5 + 2];
  }
  p.zero = 0;
  p.helpers = helpers;
  {
    const cuuint64_t dims[5] = {1024, 2, 4, 4, 128}, strides[4] = {2048, 8 * 2048, 2 * 2048, 32 * 2048};
    const cuuint32_t box[5] = {64, 2, 4, 4, 2};
    make_map(enc, &p.wo64, d_in[9], 5, dims, strides, box);
  }
  make_map2(enc, &p.o24, o_ptr, 64, 16 * 64 * 224, 24);
  make_map2(enc, &p.o88, o_ptr, 64, 16 * 64 * 224, 88);
  make_map2(enc, &p.out24, d_out, 2048, 1792, 24);
  make_map2(enc, &p.out88, d_out, 2048, 1792, 88);
  make_map2(enc, &p.o_ld, o_ptr, 64, 16 * 64 * 224, 112);
  make_map2(enc, &p.out_st, d_out, 2048, 1792, 112);
  fused_kernel<<<helpers ? 132 : 128, 384, SMEM_TOTAL>>>(p);
}
```
